```python
import torch

def _softmax(x, axis=-1):
    return torch.softmax(x, dim=axis)
def _gelu(x):
    return torch.nn.functional.gelu(x, approximate="tanh")
def _silu(x):
    return torch.nn.functional.silu(x)
def _sigmoid(x):
    return torch.sigmoid(x)
def _layernorm(x, axis=-1, eps=1e-5):
    m = x.mean(dim=axis, keepdim=True)
    v = x.var(dim=axis, keepdim=True, unbiased=False)
    return (x - m) / torch.sqrt(v + eps)
def _scatter_add(tgt, idx, src, axis=0):
    return tgt.clone().index_add_(axis, idx, src)
def _segment_sum(src, seg, n):
    out = torch.zeros((n,) + src.shape[1:], dtype=src.dtype)
    return out.index_add_(0, seg, src)
def _pad(x, pw):
    flat = tuple(v for pair in reversed(pw) for v in pair)
    return torch.nn.functional.pad(x, flat)

kernel_name = 'gated_mix__linear_attn_block__mha_block__prompt'

def setup_inputs():

    _w = (lambda a: (lambda t: t.to(torch.bfloat16) if t.is_floating_point() else t)(torch.as_tensor(a)))
    def _A_setup():
        B, S, D = 1, 2048, 640
        return {
            "x": _w((lambda *s: torch.randn(*s, dtype=torch.bfloat16) * 0.05)(B, S, D)),
            "wqkv": _w((lambda *s: torch.randn(*s, dtype=torch.bfloat16) * 0.8)(D, 3 * D)),
            "wo": _w((lambda *s: torch.randn(*s, dtype=torch.bfloat16) * 0.2)(D, D)),
        }
    _A_in = _A_setup()

    def _B_setup():
        B, S, D, H = 1, 2048, 640, 32
        return {
            "x": _w((lambda *s: torch.randn(*s, dtype=torch.bfloat16) * 0.05)(B, S, D)),
            "wqkv": _w((lambda *s: torch.randn(*s, dtype=torch.bfloat16) * 0.8)(D, 3 * D)),
            "wo": _w((lambda *s: torch.randn(*s, dtype=torch.bfloat16) * 0.05)(D, D)),
        }
    _B_in = _B_setup()

    return {
        "A_x": _A_in["x"],
        "A_wqkv": _A_in["wqkv"],
        "A_wo": _A_in["wo"],
        "B_x": _B_in["x"],
        "B_wqkv": _B_in["wqkv"],
        "B_wo": _B_in["wo"],
        "gate_w": _w((lambda *s: torch.randn(*s, dtype=torch.bfloat16) * 0.05)(640) * 16.0),
    }

def reference(A_x, A_wqkv, A_wo, B_x, B_wqkv, B_wo, gate_w):
    def _A_ref(x, wqkv, wo):
        B, S, D = x.shape
        H = 32; Dh = D // H
        qkv = (lambda x, *d: x.permute(*d))((x @ wqkv).reshape(B, S, 3, H, Dh), 2, 0, 3, 1, 4)
        q, k, v = qkv[0], qkv[1], qkv[2]
        phi = lambda t: torch.where(t > 0, t + 1, torch.exp(t)) + 1e-6
        pq, pk = phi(q), phi(k)
        kv = torch.einsum("bhsd,bhse->bhde", pk, v)
        z = torch.einsum("bhsd->bhd", pk)
        num = torch.einsum("bhqd,bhde->bhqe", pq, kv)
        den = torch.einsum("bhqd,bhd->bhq", pq, z)[..., None] + 1e-6
        o = num / den
        return (lambda x, *d: x.permute(*d))(o, 0, 2, 1, 3).reshape(B, S, D) @ wo

    def _B_ref(x, wqkv, wo):
        B, S, D = x.shape
        H = 32
        Dh = D // H
        qkv = (lambda x, *d: x.permute(*d))((x @ wqkv).reshape(B, S, 3, H, Dh), 2, 0, 3, 1, 4)
        q, k, v = qkv[0], qkv[1], qkv[2]
        scores = torch.einsum("bhqd,bhkd->bhqk", q, k) * (Dh ** -0.5)
        p = _softmax(scores, axis=-1)
        o = torch.einsum("bhqk,bhkd->bhqd", p, v)
        return (lambda x, *d: x.permute(*d))(o, 0, 2, 1, 3).reshape(B, S, D) @ wo

    x = A_x
    g = _sigmoid((x * gate_w).sum(-1, keepdims=True))
    a = _A_ref(x, A_wqkv, A_wo)
    b = _B_ref(x, B_wqkv, B_wo)
    return g * a + (1 - g) * b
```

```cpp
#include <cuda_runtime.h>
#include <cuda_bf16.h>
#include <cuda.h>
#include <stdint.h>

#define SEQ 2048
#define DM 640
#define NH 32
#define DH 20

#define POLY_MASK 0xD5D5u
#define POLY_DEG 2

__device__ __align__(1024) uint8_t g_kvimg[NH * 196608];
__device__ __align__(1024) uint8_t g_qb[SEQ * DM * 2];
__device__ __align__(1024) uint8_t g_pq[SEQ * DM * 2];
__device__ __align__(1024) uint8_t g_acat[SEQ * 2 * DM * 2 + 4096];
__device__ __align__(1024) __nv_bfloat16 g_wm[DM * DM];
__device__ __align__(16) float g_kvpart[16 * NH * 480];
__device__ __align__(16) float g_zpart[16 * NH * 20];
__device__ __align__(16) float g_kn2[NH * 128];
__device__ __align__(16) float g_gate[SEQ];

__device__ __forceinline__ uint32_t smem_u32(const void* p) { return (uint32_t)__cvta_generic_to_shared(p); }
__device__ __forceinline__ uint64_t mkdesc(uint32_t saddr, uint32_t lbo, uint32_t sbo, uint32_t swz) {
    return (uint64_t)((saddr & 0x3FFFF) >> 4) | ((uint64_t)(lbo >> 4) << 16) | ((uint64_t)(sbo >> 4) << 32) | ((uint64_t)swz << 62);
}
#define WG_FENCE() asm volatile("wgmma.fence.sync.aligned;" ::: "memory")
#define WG_COMMIT() asm volatile("wgmma.commit_group.sync.aligned;" ::: "memory")
#define WG_WAIT(n) asm volatile("wgmma.wait_group.sync.aligned %0;" :: "n"(n) : "memory")
template<int N> __device__ __forceinline__ void fence_f(float (&d)[N]) {
    #pragma unroll
    for (int i = 0; i < N; i++) asm volatile("" : "+f"(d[i]) :: "memory");
}
template<int N> __device__ __forceinline__ void fence_r(uint32_t (&d)[N]) {
    #pragma unroll
    for (int i = 0; i < N; i++) asm volatile("" : "+r"(d[i]) :: "memory");
}
__device__ __forceinline__ void mbar_init(uint32_t bar, uint32_t cnt) { asm volatile("mbarrier.init.shared::cta.b64 [%0], %1;" :: "r"(bar), "r"(cnt)); }
__device__ __forceinline__ void mbar_expect(uint32_t bar, uint32_t bytes) { asm volatile("mbarrier.arrive.expect_tx.shared::cta.b64 _, [%0], %1;" :: "r"(bar), "r"(bytes) : "memory"); }
__device__ __forceinline__ void mbar_arrive(uint32_t bar) { asm volatile("mbarrier.arrive.shared::cta.b64 _, [%0];" :: "r"(bar) : "memory"); }
__device__ __forceinline__ void mbar_wait(uint32_t bar, uint32_t parity) {
    asm volatile("{\n.reg .pred p;\nWAIT_%=:\nmbarrier.try_wait.parity.shared::cta.b64 p, [%0], %1;\n@p bra DONE_%=;\nbra WAIT_%=;\nDONE_%=:\n}" :: "r"(bar), "r"(parity) : "memory");
}
__device__ __forceinline__ void tma2d(uint32_t dst, const CUtensorMap* tm, uint32_t bar, int c0, int c1) {
    asm volatile("cp.async.bulk.tensor.2d.shared::cluster.global.mbarrier::complete_tx::bytes [%0], [%1, {%3,%4}], [%2];"
        :: "r"(dst), "l"((uint64_t)tm), "r"(bar), "r"(c0), "r"(c1) : "memory");
}
__device__ __forceinline__ void bulk_load(uint32_t dst, const void* src, uint32_t bytes, uint32_t bar) {
    asm volatile("cp.async.bulk.shared::cluster.global.mbarrier::complete_tx::bytes [%0], [%1], %2, [%3];" :: "r"(dst), "l"(src), "r"(bytes), "r"(bar) : "memory");
}
__device__ __forceinline__ void l2_prefetch(const void* src, uint32_t bytes) {
    asm volatile("cp.async.bulk.prefetch.L2.global [%0], %1;" :: "l"(src), "r"(bytes) : "memory");
}
__device__ __forceinline__ void named_bar(int id, int n) { asm volatile("bar.sync %0, %1;" :: "r"(id), "r"(n) : "memory"); }
__device__ __forceinline__ float ex2f(float x) { float y; asm("ex2.approx.ftz.f32 %0, %1;" : "=f"(y) : "f"(x)); return y; }
__device__ __forceinline__ uint32_t packbf(float lo, float hi) { uint32_t r; asm("cvt.rn.bf16x2.f32 %0, %1, %2;" : "=r"(r) : "f"(hi), "f"(lo)); return r; }
__device__ __forceinline__ float bflo(uint32_t v) { return __uint_as_float(v << 16); }
__device__ __forceinline__ float bfhi(uint32_t v) { return __uint_as_float(v & 0xFFFF0000u); }
__device__ __forceinline__ float phi_f(float t) { return (fmaxf(t, 0.f) + 1e-6f) + ex2f(fminf(t, 0.f) * 1.4426950408889634f); }
__device__ __forceinline__ uint32_t q_off(int tok, int col) { return ((tok >> 3) * 80 + (col >> 3)) * 128 + (tok & 7) * 16 + (col & 7) * 2; }
__device__ __forceinline__ uint32_t acat_off(int tok, int kk) { return (((kk >> 6) * 256 + (tok >> 3)) * 8 + ((kk >> 3) & 7)) * 128 + (tok & 7) * 16 + (kk & 7) * 2; }
#define GRIDDEP_WAIT() asm volatile("griddepcontrol.wait;" ::: "memory")
#define GRIDDEP_LAUNCH() asm volatile("griddepcontrol.launch_dependents;" ::: "memory")

#define TS_MIN(i)
#define CK(k, i)
#define CK3(i)
#define TS_MAX(i)

__device__ __forceinline__ void wg_rs_n128_bt(float (&d)[64], uint32_t a0, uint32_t a1, uint32_t a2, uint32_t a3, uint64_t db) {
    asm volatile("wgmma.mma_async.sync.aligned.m64n128k16.f32.bf16.bf16 {%0,%1,%2,%3,%4,%5,%6,%7,%8,%9,%10,%11,%12,%13,%14,%15,%16,%17,%18,%19,%20,%21,%22,%23,%24,%25,%26,%27,%28,%29,%30,%31,%32,%33,%34,%35,%36,%37,%38,%39,%40,%41,%42,%43,%44,%45,%46,%47,%48,%49,%50,%51,%52,%53,%54,%55,%56,%57,%58,%59,%60,%61,%62,%63}, {%64,%65,%66,%67}, %68, 1, 1, 1, 1;"
      : "+f"(d[0]),"+f"(d[1]),"+f"(d[2]),"+f"(d[3]),"+f"(d[4]),"+f"(d[5]),"+f"(d[6]),"+f"(d[7]),"+f"(d[8]),"+f"(d[9]),"+f"(d[10]),"+f"(d[11]),"+f"(d[12]),"+f"(d[13]),"+f"(d[14]),"+f"(d[15]),"+f"(d[16]),"+f"(d[17]),"+f"(d[18]),"+f"(d[19]),"+f"(d[20]),"+f"(d[21]),"+f"(d[22]),"+f"(d[23]),"+f"(d[24]),"+f"(d[25]),"+f"(d[26]),"+f"(d[27]),"+f"(d[28]),"+f"(d[29]),"+f"(d[30]),"+f"(d[31]),"+f"(d[32]),"+f"(d[33]),"+f"(d[34]),"+f"(d[35]),"+f"(d[36]),"+f"(d[37]),"+f"(d[38]),"+f"(d[39]),"+f"(d[40]),"+f"(d[41]),"+f"(d[42]),"+f"(d[43]),"+f"(d[44]),"+f"(d[45]),"+f"(d[46]),"+f"(d[47]),"+f"(d[48]),"+f"(d[49]),"+f"(d[50]),"+f"(d[51]),"+f"(d[52]),"+f"(d[53]),"+f"(d[54]),"+f"(d[55]),"+f"(d[56]),"+f"(d[57]),"+f"(d[58]),"+f"(d[59]),"+f"(d[60]),"+f"(d[61]),"+f"(d[62]),"+f"(d[63]) : "r"(a0), "r"(a1), "r"(a2), "r"(a3), "l"(db));
}
__device__ __forceinline__ void wg_ss_n128_bt(float (&d)[64], uint64_t da, uint64_t db, int acc) {
    asm volatile("{.reg .pred p; setp.ne.b32 p, %66, 0;\n"
      "wgmma.mma_async.sync.aligned.m64n128k16.f32.bf16.bf16 {%0,%1,%2,%3,%4,%5,%6,%7,%8,%9,%10,%11,%12,%13,%14,%15,%16,%17,%18,%19,%20,%21,%22,%23,%24,%25,%26,%27,%28,%29,%30,%31,%32,%33,%34,%35,%36,%37,%38,%39,%40,%41,%42,%43,%44,%45,%46,%47,%48,%49,%50,%51,%52,%53,%54,%55,%56,%57,%58,%59,%60,%61,%62,%63}, %64, %65, p, 1, 1, 0, 1;}"
      : "+f"(d[0]),"+f"(d[1]),"+f"(d[2]),"+f"(d[3]),"+f"(d[4]),"+f"(d[5]),"+f"(d[6]),"+f"(d[7]),"+f"(d[8]),"+f"(d[9]),"+f"(d[10]),"+f"(d[11]),"+f"(d[12]),"+f"(d[13]),"+f"(d[14]),"+f"(d[15]),"+f"(d[16]),"+f"(d[17]),"+f"(d[18]),"+f"(d[19]),"+f"(d[20]),"+f"(d[21]),"+f"(d[22]),"+f"(d[23]),"+f"(d[24]),"+f"(d[25]),"+f"(d[26]),"+f"(d[27]),"+f"(d[28]),"+f"(d[29]),"+f"(d[30]),"+f"(d[31]),"+f"(d[32]),"+f"(d[33]),"+f"(d[34]),"+f"(d[35]),"+f"(d[36]),"+f"(d[37]),"+f"(d[38]),"+f"(d[39]),"+f"(d[40]),"+f"(d[41]),"+f"(d[42]),"+f"(d[43]),"+f"(d[44]),"+f"(d[45]),"+f"(d[46]),"+f"(d[47]),"+f"(d[48]),"+f"(d[49]),"+f"(d[50]),"+f"(d[51]),"+f"(d[52]),"+f"(d[53]),"+f"(d[54]),"+f"(d[55]),"+f"(d[56]),"+f"(d[57]),"+f"(d[58]),"+f"(d[59]),"+f"(d[60]),"+f"(d[61]),"+f"(d[62]),"+f"(d[63]) : "l"(da), "l"(db), "r"(acc));
}
__device__ __forceinline__ void wg_ss_n32_bt(float (&d)[16], uint64_t da, uint64_t db, int acc) {
    asm volatile("{.reg .pred p; setp.ne.b32 p, %18, 0;\n"
      "wgmma.mma_async.sync.aligned.m64n32k16.f32.bf16.bf16 {%0,%1,%2,%3,%4,%5,%6,%7,%8,%9,%10,%11,%12,%13,%14,%15}, %16, %17, p, 1, 1, 0, 1;}"
      : "+f"(d[0]),"+f"(d[1]),"+f"(d[2]),"+f"(d[3]),"+f"(d[4]),"+f"(d[5]),"+f"(d[6]),"+f"(d[7]),"+f"(d[8]),"+f"(d[9]),"+f"(d[10]),"+f"(d[11]),"+f"(d[12]),"+f"(d[13]),"+f"(d[14]),"+f"(d[15]) : "l"(da), "l"(db), "r"(acc));
}
__device__ __forceinline__ void wg_rs_n32_bt(float (&d)[16], uint32_t a0, uint32_t a1, uint32_t a2, uint32_t a3, uint64_t db) {
    asm volatile("wgmma.mma_async.sync.aligned.m64n32k16.f32.bf16.bf16 {%0,%1,%2,%3,%4,%5,%6,%7,%8,%9,%10,%11,%12,%13,%14,%15}, {%16,%17,%18,%19}, %20, 1, 1, 1, 1;"
      : "+f"(d[0]),"+f"(d[1]),"+f"(d[2]),"+f"(d[3]),"+f"(d[4]),"+f"(d[5]),"+f"(d[6]),"+f"(d[7]),"+f"(d[8]),"+f"(d[9]),"+f"(d[10]),"+f"(d[11]),"+f"(d[12]),"+f"(d[13]),"+f"(d[14]),"+f"(d[15]) : "r"(a0), "r"(a1), "r"(a2), "r"(a3), "l"(db));
}
__device__ __forceinline__ void wg_ss_n88_atbt(float (&d)[44], uint64_t da, uint64_t db, int acc) {
    asm volatile("{.reg .pred p; setp.ne.b32 p, %46, 0;\n"
      "wgmma.mma_async.sync.aligned.m64n88k16.f32.bf16.bf16 {%0,%1,%2,%3,%4,%5,%6,%7,%8,%9,%10,%11,%12,%13,%14,%15,%16,%17,%18,%19,%20,%21,%22,%23,%24,%25,%26,%27,%28,%29,%30,%31,%32,%33,%34,%35,%36,%37,%38,%39,%40,%41,%42,%43}, %44, %45, p, 1, 1, 1, 1;}"
      : "+f"(d[0]),"+f"(d[1]),"+f"(d[2]),"+f"(d[3]),"+f"(d[4]),"+f"(d[5]),"+f"(d[6]),"+f"(d[7]),"+f"(d[8]),"+f"(d[9]),"+f"(d[10]),"+f"(d[11]),"+f"(d[12]),"+f"(d[13]),"+f"(d[14]),"+f"(d[15]),"+f"(d[16]),"+f"(d[17]),"+f"(d[18]),"+f"(d[19]),"+f"(d[20]),"+f"(d[21]),"+f"(d[22]),"+f"(d[23]),"+f"(d[24]),"+f"(d[25]),"+f"(d[26]),"+f"(d[27]),"+f"(d[28]),"+f"(d[29]),"+f"(d[30]),"+f"(d[31]),"+f"(d[32]),"+f"(d[33]),"+f"(d[34]),"+f"(d[35]),"+f"(d[36]),"+f"(d[37]),"+f"(d[38]),"+f"(d[39]),"+f"(d[40]),"+f"(d[41]),"+f"(d[42]),"+f"(d[43]) : "l"(da), "l"(db), "r"(acc));
}
__device__ __forceinline__ void wg_ss_n8_atbt(float (&d)[4], uint64_t da, uint64_t db, int acc) {
    asm volatile("{.reg .pred p; setp.ne.b32 p, %6, 0;\n"
      "wgmma.mma_async.sync.aligned.m64n8k16.f32.bf16.bf16 {%0,%1,%2,%3}, %4, %5, p, 1, 1, 1, 1;}"
      : "+f"(d[0]),"+f"(d[1]),"+f"(d[2]),"+f"(d[3]) : "l"(da), "l"(db), "r"(acc));
}
__device__ __forceinline__ void wg_ss_n80_at(float (&d)[40], uint64_t da, uint64_t db, int acc) {
    asm volatile("{.reg .pred p; setp.ne.b32 p, %42, 0;\n"
      "wgmma.mma_async.sync.aligned.m64n80k16.f32.bf16.bf16 {%0,%1,%2,%3,%4,%5,%6,%7,%8,%9,%10,%11,%12,%13,%14,%15,%16,%17,%18,%19,%20,%21,%22,%23,%24,%25,%26,%27,%28,%29,%30,%31,%32,%33,%34,%35,%36,%37,%38,%39}, %40, %41, p, 1, 1, 1, 0;}"
      : "+f"(d[0]),"+f"(d[1]),"+f"(d[2]),"+f"(d[3]),"+f"(d[4]),"+f"(d[5]),"+f"(d[6]),"+f"(d[7]),"+f"(d[8]),"+f"(d[9]),"+f"(d[10]),"+f"(d[11]),"+f"(d[12]),"+f"(d[13]),"+f"(d[14]),"+f"(d[15]),"+f"(d[16]),"+f"(d[17]),"+f"(d[18]),"+f"(d[19]),"+f"(d[20]),"+f"(d[21]),"+f"(d[22]),"+f"(d[23]),"+f"(d[24]),"+f"(d[25]),"+f"(d[26]),"+f"(d[27]),"+f"(d[28]),"+f"(d[29]),"+f"(d[30]),"+f"(d[31]),"+f"(d[32]),"+f"(d[33]),"+f"(d[34]),"+f"(d[35]),"+f"(d[36]),"+f"(d[37]),"+f"(d[38]),"+f"(d[39]) : "l"(da), "l"(db), "r"(acc));
}
__device__ __forceinline__ void wg_qk0(float (&d)[32], uint32_t a0, uint32_t a1, uint32_t a2, uint32_t a3, uint64_t db) {
    asm volatile("wgmma.mma_async.sync.aligned.m64n64k16.f32.bf16.bf16 {%0,%1,%2,%3,%4,%5,%6,%7,%8,%9,%10,%11,%12,%13,%14,%15,%16,%17,%18,%19,%20,%21,%22,%23,%24,%25,%26,%27,%28,%29,%30,%31}, {%32,%33,%34,%35}, %36, 0, 1, 1, 0;"
      : "+f"(d[0]),"+f"(d[1]),"+f"(d[2]),"+f"(d[3]),"+f"(d[4]),"+f"(d[5]),"+f"(d[6]),"+f"(d[7]),"+f"(d[8]),"+f"(d[9]),"+f"(d[10]),"+f"(d[11]),"+f"(d[12]),"+f"(d[13]),"+f"(d[14]),"+f"(d[15]),"+f"(d[16]),"+f"(d[17]),"+f"(d[18]),"+f"(d[19]),"+f"(d[20]),"+f"(d[21]),"+f"(d[22]),"+f"(d[23]),"+f"(d[24]),"+f"(d[25]),"+f"(d[26]),"+f"(d[27]),"+f"(d[28]),"+f"(d[29]),"+f"(d[30]),"+f"(d[31]) : "r"(a0), "r"(a1), "r"(a2), "r"(a3), "l"(db));
}
__device__ __forceinline__ void wg_qk1(float (&d)[32], uint32_t a0, uint32_t a1, uint32_t a2, uint32_t a3, uint64_t db) {
    asm volatile("wgmma.mma_async.sync.aligned.m64n64k16.f32.bf16.bf16 {%0,%1,%2,%3,%4,%5,%6,%7,%8,%9,%10,%11,%12,%13,%14,%15,%16,%17,%18,%19,%20,%21,%22,%23,%24,%25,%26,%27,%28,%29,%30,%31}, {%32,%33,%34,%35}, %36, 1, 1, 1, 0;"
      : "+f"(d[0]),"+f"(d[1]),"+f"(d[2]),"+f"(d[3]),"+f"(d[4]),"+f"(d[5]),"+f"(d[6]),"+f"(d[7]),"+f"(d[8]),"+f"(d[9]),"+f"(d[10]),"+f"(d[11]),"+f"(d[12]),"+f"(d[13]),"+f"(d[14]),"+f"(d[15]),"+f"(d[16]),"+f"(d[17]),"+f"(d[18]),"+f"(d[19]),"+f"(d[20]),"+f"(d[21]),"+f"(d[22]),"+f"(d[23]),"+f"(d[24]),"+f"(d[25]),"+f"(d[26]),"+f"(d[27]),"+f"(d[28]),"+f"(d[29]),"+f"(d[30]),"+f"(d[31]) : "r"(a0), "r"(a1), "r"(a2), "r"(a3), "l"(db));
}
__device__ __forceinline__ void wg_pv(float (&d)[12], uint32_t a0, uint32_t a1, uint32_t a2, uint32_t a3, uint64_t db) {
    asm volatile("wgmma.mma_async.sync.aligned.m64n24k16.f32.bf16.bf16 {%0,%1,%2,%3,%4,%5,%6,%7,%8,%9,%10,%11}, {%12,%13,%14,%15}, %16, 1, 1, 1, 1;"
      : "+f"(d[0]),"+f"(d[1]),"+f"(d[2]),"+f"(d[3]),"+f"(d[4]),"+f"(d[5]),"+f"(d[6]),"+f"(d[7]),"+f"(d[8]),"+f"(d[9]),"+f"(d[10]),"+f"(d[11]) : "r"(a0), "r"(a1), "r"(a2), "r"(a3), "l"(db));
}

#define K1_STG 131072
#define K1_ONES 229376
#define K1_BARS 229632
#define K1_SMEM 229888
#define QSCALE 0.32259799f

__device__ __forceinline__ void tma4d(uint32_t dst, const CUtensorMap* tm, uint32_t bar, int c0, int c1, int c2, int c3) {
    asm volatile("cp.async.bulk.tensor.4d.shared::cluster.global.mbarrier::complete_tx::bytes [%0], [%1, {%3,%4,%5,%6}], [%2];"
        :: "r"(dst), "l"((uint64_t)tm), "r"(bar), "r"(c0), "r"(c1), "r"(c2), "r"(c3) : "memory");
}
__device__ __forceinline__ int k1_qs(int kb) { return (0x1043210210ull >> (4 * kb)) & 7; }
__device__ __forceinline__ uint32_t k1_qslot(int s) { return s * 40960 + (s >= 3 ? 8192 : 0); }
__device__ __forceinline__ void k1_issue(int pass, int kb, uint32_t sb, const CUtensorMap* tx, const CUtensorMap* tw, int mt, int hg) {
    const int s = pass ? k1_qs(kb) : (kb + 2) % 3;
    const uint32_t st = sb + (pass ? k1_qslot(s) : s * 65536), fb = sb + K1_BARS + pass * 48 + 8 * s;
    mbar_expect(fb, pass ? 40960 : 65536);
    tma2d(st, tx, fb, kb * 64, mt * 128);
    tma4d(st + 16384, tw + pass, fb, 0, kb * 64, (hg * 160) >> 6, 1 - pass);
}
__device__ __forceinline__ void stsm4(uint32_t addr, uint32_t r0, uint32_t r1, uint32_t r2, uint32_t r3) {
    asm volatile("stmatrix.sync.aligned.m8n8.x4.shared.b16 [%0], {%1,%2,%3,%4};" :: "r"(addr), "r"(r0), "r"(r1), "r"(r2), "r"(r3) : "memory");
}
__device__ __forceinline__ void bulk_store(void* dst, uint32_t src, uint32_t bytes) {
    asm volatile("cp.async.bulk.global.shared::cta.bulk_group [%0], [%1], %2;" :: "l"(dst), "r"(src), "r"(bytes) : "memory");
}
#define FENCE_ASYNC() asm volatile("fence.proxy.async.shared::cta;" ::: "memory")

__device__ __forceinline__ void k1_pass(uint32_t (&pk)[40], uint32_t sb, int pass, uint32_t a_off, uint32_t b_off, bool odd, int mode, int lane,
                                        bool producer, const CUtensorMap* tx, const CUtensorMap* tw, int mt, int hg) {
    float a0[64], a2[16];
    #pragma unroll
    for (int i = 0; i < 64; i++) a0[i] = 0.f;
    #pragma unroll
    for (int i = 0; i < 16; i++) a2[i] = 0.f;
    fence_f(a0); fence_f(a2);
    const uint32_t o0 = odd ? 512 : 0, o2 = odd ? 4 : 1024;
    if (pass == 0) {
        for (int kb = 0; kb < 10; kb++) {
            const int s = (kb + 2) % 3;
            mbar_wait(sb + K1_BARS + 8 * s, (kb / 3) & 1);
            const uint32_t st = sb + s * 65536;
            const uint64_t db = mkdesc(st + b_off, 8192, 1024, 1);
            uint32_t af[4][4];
            #pragma unroll
            for (int k = 0; k < 4; k++)
                asm volatile("ldmatrix.sync.aligned.m8n8.x4.shared.b16 {%0,%1,%2,%3}, [%4];"
                    : "=r"(af[k][0]), "=r"(af[k][1]), "=r"(af[k][2]), "=r"(af[k][3]) : "r"(st + a_off + (((2 * k + (lane >> 4)) ^ (lane & 7)) << 4)));
            WG_FENCE();
            #pragma unroll
            for (int k = 0; k < 4; k++) {
                wg_rs_n128_bt(a0, af[k][0], af[k][1], af[k][2], af[k][3], db + o0 + k * 128);
                wg_rs_n32_bt(a2, af[k][0], af[k][1], af[k][2], af[k][3], db + o2 + k * 128);
            }
            WG_COMMIT();
            WG_WAIT(0);
            const uint32_t eb = sb + K1_BARS + (kb == 9 ? 128 : 24 + 8 * s);
            if (lane == 0) mbar_arrive(eb);
            if (producer && kb < 9) {
                mbar_wait(eb, (kb / 3) & 1);
                if (kb < 7) k1_issue(0, kb + 3, sb, tx, tw, mt, hg);
                else { k1_issue(1, kb - 7, sb, tx, tw, mt, hg); if (kb == 8) k1_issue(1, 2, sb, tx, tw, mt, hg); }
            }
            __syncwarp();
        }
    } else {
        for (int kb = 0; kb < 10; kb++) {
            const int s = k1_qs(kb);
            mbar_wait(sb + K1_BARS + 48 + 8 * s, (kb >= 3 && kb < 6) ? 1 : 0);
            CK(0, 6 + (kb & 7));
            const uint32_t st = sb + k1_qslot(s);
            const uint64_t da = mkdesc(st + a_off, 16, 1024, 1), db = mkdesc(st + b_off, 8192, 1024, 1);
            WG_FENCE();
            #pragma unroll
            for (int k = 0; k < 4; k++) {
                wg_ss_n128_bt(a0, da + k * 2, db + o0 + k * 128, 1);
                wg_ss_n32_bt(a2, da + k * 2, db + o2 + k * 128, 1);
            }
            WG_COMMIT();
            WG_WAIT(1);
            if (kb > 0 && kb < 7) {
                const uint32_t eb = sb + K1_BARS + 88 + 8 * ((kb - 1) % 3);
                if (lane == 0) mbar_arrive(eb);
                if (producer && kb < 6) { mbar_wait(eb, kb > 3 ? 1 : 0); k1_issue(1, kb < 4 ? kb + 2 : kb + 4, sb, tx, tw, mt, hg); }
                __syncwarp();
            }
        }
        WG_WAIT(0);
    }
    fence_f(a0); fence_f(a2);
    if (mode == 1) {
        #pragma unroll
        for (int i = 0; i < 32; i++) pk[i] = packbf(phi_f(a0[2 * i]), phi_f(a0[2 * i + 1]));
        #pragma unroll
        for (int i = 0; i < 8; i++) pk[32 + i] = packbf(phi_f(a2[2 * i]), phi_f(a2[2 * i + 1]));
    } else {
        const float sc = mode == 2 ? QSCALE : 1.f;
        #pragma unroll
        for (int i = 0; i < 32; i++) pk[i] = packbf(a0[2 * i] * sc, a0[2 * i + 1] * sc);
        #pragma unroll
        for (int i = 0; i < 8; i++) pk[32 + i] = packbf(a2[2 * i] * sc, a2[2 * i + 1] * sc);
    }
}
__device__ __forceinline__ void k1_stage_rows(const uint32_t (&pk)[40], uint32_t base, bool odd) {
    const uint32_t b0 = base + (odd ? 512 : 0), b2 = base + (odd ? 0 : 2048);
    #pragma unroll
    for (int j = 0; j < 16; j += 2) stsm4(b0 + j * 128, pk[2*j], pk[2*j+1], pk[2*j+2], pk[2*j+3]);
    #pragma unroll
    for (int j = 0; j < 4; j += 2) stsm4(b2 + j * 128, pk[32 + 2*j], pk[33 + 2*j], pk[34 + 2*j], pk[35 + 2*j]);
}
template<bool ODD>
__device__ __forceinline__ void k1_image(const uint32_t (&pk)[40], uint32_t base, int lane) {
    #define PH(j) (ODD ? ((j) < 4 ? (j) + 16 : (j) - 4) : (j))
    const bool hi = lane & 16;
    #pragma unroll
    for (int i = 0; i < 4; i++) {
        const uint32_t e = base + (2 * i) * 12288, o = e + 12288;
        const int j = 5 * i;
        stsm4(hi ? e + 128 : e, pk[2*PH(j)], pk[2*PH(j)+1], pk[2*PH(j+1)], pk[2*PH(j+1)+1]);
        stsm4(hi ? o : e + 256, pk[2*PH(j+2)], pk[2*PH(j+2)+1], pk[2*PH(j+2)], pk[2*PH(j+2)+1]);
        stsm4(hi ? o + 256 : o + 128, pk[2*PH(j+3)], pk[2*PH(j+3)+1], pk[2*PH(j+4)], pk[2*PH(j+4)+1]);
    }
}
template<bool ODD>
__device__ __forceinline__ void k1_norms(const uint32_t (&pk)[40], int lane, float* kn_dst) {
    {
        const bool lo = (lane & 3) < 2;
        #pragma unroll
        for (int h = 0; h < 8; h++) {
            float a = 0.f, b = 0.f;
            #pragma unroll
            for (int jj = 0; jj < 3; jj++) {
                const int j = (5 * h) / 2 + jj;
                const uint32_t v0 = pk[2*PH(j)], v1 = pk[2*PH(j)+1];
                float s0 = bflo(v0) * bflo(v0) + bfhi(v0) * bfhi(v0), s1 = bflo(v1) * bflo(v1) + bfhi(v1) * bfhi(v1);
                if (jj == ((h & 1) ? 0 : 2)) { const bool mine = (h & 1) ? !lo : lo; s0 = mine ? s0 : 0.f; s1 = mine ? s1 : 0.f; }
                a += s0; b += s1;
            }
            a += __shfl_xor_sync(0xffffffffu, a, 1); b += __shfl_xor_sync(0xffffffffu, b, 1);
            a += __shfl_xor_sync(0xffffffffu, a, 2); b += __shfl_xor_sync(0xffffffffu, b, 2);
            a = fmaxf(a, b);
            a = fmaxf(a, __shfl_xor_sync(0xffffffffu, a, 4));
            a = fmaxf(a, __shfl_xor_sync(0xffffffffu, a, 8));
            a = fmaxf(a, __shfl_xor_sync(0xffffffffu, a, 16));
            if (lane == h) kn_dst[h * 128] = a;
        }
    }
    #undef PH
}

#define K1_BAR(i) (sb + K1_BARS + 8 * (i))
struct WMaps { CUtensorMap m[4]; };
__global__ void __launch_bounds__(512, 1)
qkv_kernel(const __grid_constant__ CUtensorMap tm_x, const __grid_constant__ WMaps tm_w,
           const __nv_bfloat16* __restrict__ x, const __nv_bfloat16* __restrict__ gate_w,
           const __nv_bfloat16* __restrict__ woa, const __nv_bfloat16* __restrict__ wob) {
    extern __shared__ __align__(1024) uint8_t smem[];
    const uint32_t sb = smem_u32(smem);
    const int tid = threadIdx.x, warp = tid >> 5, lane = tid & 31;
    const int mt = ((blockIdx.x >> 4) & 3) * 4 + (blockIdx.x & 3), grp = (blockIdx.x >> 6) * 4 + ((blockIdx.x >> 2) & 3), br = grp >> 2, hg = grp & 3;
    TS_MIN(0); CK(0, 0);
    if (tid == 0) {
        for (int i = 0; i < 3; i++) { mbar_init(K1_BAR(i), 1); mbar_init(K1_BAR(3 + i), 16); }
        for (int i = 0; i < 5; i++) { mbar_init(K1_BAR(6 + i), 1); mbar_init(K1_BAR(11 + i), 8); }
        mbar_init(K1_BAR(16), 16); mbar_init(K1_BAR(17), 16); mbar_init(K1_BAR(18), 8); mbar_init(K1_BAR(19), 8); mbar_init(K1_BAR(20), 8);
        asm volatile("fence.mbarrier_init.release.cluster;" ::: "memory");
    }
    __syncthreads();
    GRIDDEP_LAUNCH();
    const CUtensorMap* tw = &tm_w.m[br * 2];
    if (tid == 0) for (int i = 0; i < 3; i++) k1_issue(0, i, sb, &tm_x, tw, mt, hg);
    if (tid == 32) {
        l2_prefetch(woa + blockIdx.x * 5 * DM, 6400);
        l2_prefetch(wob + blockIdx.x * 5 * DM, 6400);
    }
    __syncwarp();
    {
        if (tid < 32) *(uint32_t*)(smem + K1_ONES + lane * 4) = (lane & 3) == 0 ? 0x3F80u : 0u;
        const int wg = __shfl_sync(0xffffffffu, warp >> 2, 0), mh = wg & 1, sel = wg >> 1, w4 = warp & 3;
        const int g = lane >> 2, t = lane & 3;
        const int rg = mh * 8 + w4 * 2 + ((lane >> 3) & 1);
        const uint32_t arow = (mh * 64 + w4 * 16 + (lane & 15)) * 128;
        CK(0, 1);
        {
            uint32_t pk[40];
            k1_pass(pk, sb, 0, arow, 16384 + sel * 24576, hg & 1, (br == 0 && sel == 0) ? 1 : 0, lane, tid == 0, &tm_x, tw, mt, hg);
            CK(0, 2);
            mbar_wait(K1_BAR(16), 0);
            if (br) {
                const uint32_t base = sb + K1_STG + rg * 768 + sel * 384 + (lane & 7) * 16;
                if (hg & 1) k1_image<true>(pk, base, lane); else k1_image<false>(pk, base, lane);
                __syncwarp();
                {
                    const int lr = mh * 64 + w4 * 16 + (lane & 15);
                    const uint32_t flag = (sel == 0 && ((POLY_MASK >> ((lr >> 3) & 15)) & 1)) ? 0x3F80u : 0u;
                    const uint2 cv = make_uint2(0x3F80u | (flag << 16), flag);
                    uint8_t* p = smem + K1_STG + (lane >> 4) * 49152 + (lr >> 3) * 768 + sel * 384 + (lr & 7) * 16;
                    *(uint2*)(p + 264) = cv; *(uint2*)(p + 12288) = cv; *(uint2*)(p + 24576 + 264) = cv; *(uint2*)(p + 36864) = cv;
                }
                __syncwarp();
                if (lane == 0) mbar_arrive(K1_BAR(17));
                if (sel == 0) {
                    float* kd = g_kn2 + (hg * 8) * 128 + mt * 8 + mh * 4 + w4;
                    if (hg & 1) k1_norms<true>(pk, lane, kd); else k1_norms<false>(pk, lane, kd);
                    mbar_wait(K1_BAR(17), 0);
                    #pragma unroll 8
                    for (int i = 0; i < 24; i++) {
                        const int h = i / 3, o = (i % 3) * 4096 + tid * 16;
                        *(uint4*)(g_kvimg + (size_t)(hg * 8 + h) * 196608 + mt * 12288 + o) = *(const uint4*)(smem + K1_STG + h * 12288 + o);
                    }
                    FENCE_ASYNC();
                    named_bar(1, 256);
                    if (tid == 0) { k1_issue(1, 6, sb, &tm_x, tw, mt, hg); k1_issue(1, 7, sb, &tm_x, tw, mt, hg); }
                }
            } else {
                const uint32_t base = sb + K1_STG + rg * 5120 + sel * 2560 + (lane >> 4) * 128 + (lane & 7) * 16;
                k1_stage_rows(pk, base, hg & 1);
                FENCE_ASYNC();
                __syncwarp();
                if (lane == 0) mbar_arrive(K1_BAR(17));
                if (sel == 0) {
                    mbar_wait(K1_BAR(17), 0);
                    float* kvo = (float*)(smem + K1_STG + 81920);
                    #pragma unroll 1
                    for (int mi = wg; mi < 3; mi += 2) {
                        float kv[44], zz[4];
                        #pragma unroll
                        for (int i = 0; i < 44; i++) kv[i] = 0.f;
                        zz[0] = zz[1] = zz[2] = zz[3] = 0.f;
                        fence_f(kv); fence_f(zz);
                        const int vs = mi == 0 ? 0 : (mi == 1 ? 56 : 72);
                        const uint64_t da = mkdesc(sb + K1_STG + mi * 1024, 5120, 128, 0);
                        const uint64_t db = mkdesc(sb + K1_STG + 2560 + (vs >> 3) * 128, 5120, 128, 0);
                        const uint64_t d1 = mkdesc(sb + K1_ONES, 0, 128, 0);
                        WG_FENCE();
                        #pragma unroll
                        for (int k = 0; k < 8; k++) {
                            wg_ss_n88_atbt(kv, da + k * 640, db + k * 640, 1);
                            wg_ss_n8_atbt(zz, da + k * 640, d1, 1);
                        }
                        WG_COMMIT();
                        WG_WAIT(0);
                        fence_f(kv); fence_f(zz);
                        #pragma unroll
                        for (int r = 0; r < 2; r++) {
                            const int pc = mi * 64 + w4 * 16 + g + 8 * r;
                            if (pc < 160) {
                                const int e0 = vs + 2 * t - (pc / 20) * 20;
                                #pragma unroll
                                for (int j = 0; j < 11; j++) {
                                    const int e = e0 + 8 * j;
                                    if (e >= 0 && e < 20) *(float2*)(kvo + pc * 24 + e) = make_float2(kv[4*j + 2*r], kv[4*j + 2*r + 1]);
                                }
                                if (t == 0) kvo[3840 + pc] = zz[2 * r];
                            }
                        }
                    }
                    FENCE_ASYNC();
                    __syncwarp();
                    if (lane == 0) mbar_arrive(K1_BAR(18));
                    if (tid == 0) {
                        mbar_wait(K1_BAR(18), 0);
                        k1_issue(1, 6, sb, &tm_x, tw, mt, hg); k1_issue(1, 7, sb, &tm_x, tw, mt, hg);
                        bulk_store(g_kvpart + (size_t)(mt * NH + hg * 8) * 480, sb + K1_STG + 81920, 15360);
                        bulk_store(g_zpart + (mt * NH + hg * 8) * 20, sb + K1_STG + 97280, 640);
                        asm volatile("cp.async.bulk.commit_group;" ::: "memory");
                    }
                }
            }
        }
        CK(0, 3);
        if (sel == 1) {
            uint32_t pk[40];
            k1_pass(pk, sb, 1, mh * 8192, 16384, hg & 1, br ? 2 : 1, lane, tid == 256, &tm_x, tw, mt, hg);
            CK(0, 4);
            mbar_wait(K1_BAR(13), 1);
            const uint32_t qst = sb + 81920 + rg * 2560 + (lane >> 4) * 128 + (lane & 7) * 16;
            k1_stage_rows(pk, qst, hg & 1);
            FENCE_ASYNC();
            __syncwarp();
            if (lane == 0) mbar_arrive(K1_BAR(19));
            if (warp == 8 && lane < 16) {
                mbar_wait(K1_BAR(19), 0);
                bulk_store((br ? g_qb : g_pq) + ((mt * 16 + lane) * 80 + hg * 20) * 128, sb + 81920 + lane * 2560, 2560);
                asm volatile("cp.async.bulk.commit_group;" ::: "memory");
                asm volatile("cp.async.bulk.wait_group.read 0;" ::: "memory");
            }
        } else {
            const int row = mt * 128 + grp * 16 + warp * 2;
            float s0 = 0.f, s1 = 0.f;
            uint4 v0[3], v1[3], w[3];
            #pragma unroll
            for (int c = 0; c < 3; c++) {
                const int ch = min(lane + 32 * c, 79);
                v0[c] = *(const uint4*)(x + row * DM + ch * 8); v1[c] = *(const uint4*)(x + (row + 1) * DM + ch * 8); w[c] = *(const uint4*)(gate_w + ch * 8);
            }
            if (lane >= 16) w[2] = make_uint4(0, 0, 0, 0);
            #pragma unroll
            for (int c = 0; c < 3; c++) {
                s0 += bflo(v0[c].x) * bflo(w[c].x) + bfhi(v0[c].x) * bfhi(w[c].x) + bflo(v0[c].y) * bflo(w[c].y) + bfhi(v0[c].y) * bfhi(w[c].y)
                    + bflo(v0[c].z) * bflo(w[c].z) + bfhi(v0[c].z) * bfhi(w[c].z) + bflo(v0[c].w) * bflo(w[c].w) + bfhi(v0[c].w) * bfhi(w[c].w);
                s1 += bflo(v1[c].x) * bflo(w[c].x) + bfhi(v1[c].x) * bfhi(w[c].x) + bflo(v1[c].y) * bflo(w[c].y) + bfhi(v1[c].y) * bfhi(w[c].y)
                    + bflo(v1[c].z) * bflo(w[c].z) + bfhi(v1[c].z) * bfhi(w[c].z) + bflo(v1[c].w) * bflo(w[c].w) + bfhi(v1[c].w) * bfhi(w[c].w);
            }
            #pragma unroll
            for (int o = 16; o; o >>= 1) { s0 += __shfl_xor_sync(0xffffffffu, s0, o); s1 += __shfl_xor_sync(0xffffffffu, s1, o); }
            if (lane < 2) g_gate[row + lane] = 1.f / (1.f + __expf(-(lane ? s1 : s0)));
            if (tid == 0) asm volatile("cp.async.bulk.wait_group.read 0;" ::: "memory");
        }
        TS_MAX(3); CK(0, 5);
    }
}

#define K2_SMEM (196608 + 1024)
struct PolyC { uint32_t one, cm15, c3, c2, c1, c0; };
__device__ __forceinline__ uint32_t hfma2bf(uint32_t a, uint32_t b, uint32_t c) { uint32_t r; asm("fma.rn.bf16x2 %0, %1, %2, %3;" : "=r"(r) : "r"(a), "r"(b), "r"(c)); return r; }
__device__ __forceinline__ uint32_t hadd2bf(uint32_t a, uint32_t b) { uint32_t r; asm("add.rn.bf16x2 %0, %1, %2;" : "=r"(r) : "r"(a), "r"(b)); return r; }
__device__ __forceinline__ uint32_t exp2_poly2(float y0, float y1, const PolyC& pc) {
    const uint32_t sch = __byte_perm(__float_as_uint(y0), __float_as_uint(y1), 0x6521);
    uint32_t m; asm("lop3.b32 %0, %1, 0x007F007F, %2, 0xEA;" : "=r"(m) : "r"(sch), "r"(pc.one));
    const uint32_t d = hadd2bf(m, pc.cm15);
    uint32_t r = hfma2bf(d, pc.c2, pc.c1);
    r = hfma2bf(r, d, pc.c0);
    return r + sch;
}
template<int PAR>
__device__ __forceinline__ void softmax_blk(const float (&s)[32], uint32_t (&p)[16], const PolyC& pc) {
    #pragma unroll
    for (int j = 0; j < 8; j++) {
        if ((POLY_MASK >> (PAR * 8 + j)) & 1) {
            p[2*j] = exp2_poly2(s[4*j], s[4*j+1], pc);
            p[2*j+1] = exp2_poly2(s[4*j+2], s[4*j+3], pc);
        } else {
            p[2*j] = packbf(ex2f(s[4*j]), ex2f(s[4*j+1]));
            p[2*j+1] = packbf(ex2f(s[4*j+2]), ex2f(s[4*j+3]));
        }
    }
}

__device__ __noinline__ void aux_work(uint8_t* smem, int ax, const __nv_bfloat16* __restrict__ a_wo) {
    float* kvs = (float*)smem;
    const int tid = threadIdx.x;
    for (int i = tid; i < 3840; i += 512) {
        float s = 0.f;
        #pragma unroll
        for (int m = 0; m < 16; m++) s += g_kvpart[(size_t)(m * NH + ax * 8) * 480 + i];
        kvs[i] = s;
    }
    __syncthreads();
    #pragma unroll 1
    for (int it = tid; it < 8 * 5 * 80; it += 512) {
        const int cc = it % 80, dq = (it / 80) % 5, h = it / 400;
        float a[4][8];
        #pragma unroll
        for (int r = 0; r < 4; r++)
            #pragma unroll
            for (int i = 0; i < 8; i++) a[r][i] = 0.f;
        const __nv_bfloat16* wp = a_wo + (size_t)((ax * 8 + h) * DH) * DM + cc * 8;
        const float* kp = kvs + (h * 20 + dq * 4) * 24;
        #pragma unroll 5
        for (int e = 0; e < 20; e++) {
            const uint4 w = *(const uint4*)(wp + e * DM);
            const float wf[8] = {bflo(w.x), bfhi(w.x), bflo(w.y), bfhi(w.y), bflo(w.z), bfhi(w.z), bflo(w.w), bfhi(w.w)};
            #pragma unroll
            for (int r = 0; r < 4; r++) {
                const float k = kp[r * 24 + e];
                #pragma unroll
                for (int i = 0; i < 8; i++) a[r][i] += k * wf[i];
            }
        }
        #pragma unroll
        for (int r = 0; r < 4; r++)
            *(uint4*)(g_wm + (size_t)((ax * 8 + h) * DH + dq * 4 + r) * DM + cc * 8) =
                make_uint4(packbf(a[r][0], a[r][1]), packbf(a[r][2], a[r][3]), packbf(a[r][4], a[r][5]), packbf(a[r][6], a[r][7]));
    }
}

__global__ void __launch_bounds__(512, 1)
attn_kernel(const __nv_bfloat16* __restrict__ a_wo) {
    extern __shared__ __align__(1024) uint8_t smem[];
    const uint32_t sb = smem_u32(smem);
    const uint32_t bars = sb + 196608;
    const int tid = threadIdx.x, warp = tid >> 5, lane = tid & 31;
    GRIDDEP_LAUNCH();
    if (blockIdx.x < 4) {
        GRIDDEP_WAIT();
        aux_work(smem, blockIdx.x, a_wo);
        TS_MAX(13);
        return;
    }
    const int h = (blockIdx.x - 4) >> 2, qb = blockIdx.x & 3;
    if (tid == 0) {
        for (int i = 0; i < 16; i++) mbar_init(bars + 8 * i, 1);
        asm volatile("fence.mbarrier_init.release.cluster;" ::: "memory");
    }
    TS_MIN(4);
    GRIDDEP_WAIT();
    TS_MIN(5); TS_MAX(17); CK(1, 0);
    const int wg = warp >> 2, w4 = warp & 3, g = lane >> 2, t = lane & 3;
    const uint8_t* kvsrc = g_kvimg + (size_t)h * 196608;
    if (tid == 0) {
        for (int i = 0; i < 2; i++) { mbar_expect(bars + 8 * i, 12288); bulk_load(sb + i * 12288, kvsrc + i * 12288, 12288, bars + 8 * i); }
    }
    const int rbase = qb * 512 + wg * 128 + w4 * 16 + g;
    const int fb = (5 * h) >> 1;
    const bool odd = h & 1;
    const bool cslot = odd ? t < 2 : t >= 2;
    uint32_t qv[4][3];
    float gt[4], kmax;
    {
        const uint32_t qo = ((rbase >> 3) * 80 + fb) * 128 + lane * 4;
        uint32_t pv[4][3];
        #pragma unroll
        for (int r = 0; r < 4; r++) {
            const uint32_t ro = qo + ((r & 1) + (r >> 1) * 8) * 10240;
            qv[r][0] = *(const uint32_t*)(g_qb + ro); qv[r][1] = *(const uint32_t*)(g_qb + ro + 128); qv[r][2] = *(const uint32_t*)(g_qb + ro + 256);
            pv[r][0] = *(const uint32_t*)(g_pq + ro); pv[r][1] = *(const uint32_t*)(g_pq + ro + 128); pv[r][2] = *(const uint32_t*)(g_pq + ro + 256);
            gt[r] = g_gate[rbase + (r & 1) * 8 + (r >> 1) * 64];
        }
        float zs = 0.f;
        {
            const int d = lane - (odd ? 4 : 0);
            if (d >= 0 && d < 20) {
                #pragma unroll
                for (int m = 0; m < 16; m++) zs += g_zpart[(m * NH + h) * 20 + d];
            }
        }
        const float4 kn4 = *(const float4*)(g_kn2 + h * 128 + lane * 4);
        float kn = fmaxf(fmaxf(kn4.x, kn4.y), fmaxf(kn4.z, kn4.w));
        #pragma unroll
        for (int o = 16; o; o >>= 1) kn = fmaxf(kn, __shfl_xor_sync(0xffffffffu, kn, o));
        kmax = sqrtf(kn);
        if (cslot) {
            #pragma unroll
            for (int r = 0; r < 4; r++) { if (odd) qv[r][0] = 0u; else qv[r][2] = 0u; }
        }
        CK(1, 3);
        __syncthreads();
        CK(1, 4);
        if (tid == 0) {
            for (int i = 2; i < 16; i++) { mbar_expect(bars + 8 * i, 12288); bulk_load(sb + i * 12288, kvsrc + i * 12288, 12288, bars + 8 * i); }
        }
        __syncwarp();
        float z[6];
        #pragma unroll
        for (int j = 0; j < 3; j++) { z[2*j] = __shfl_sync(0xffffffffu, zs, 8 * j + 2 * t); z[2*j+1] = __shfl_sync(0xffffffffu, zs, 8 * j + 2 * t + 1); }
        #pragma unroll
        for (int r = 0; r < 4; r++) {
            float den = bflo(pv[r][0]) * z[0] + bfhi(pv[r][0]) * z[1] + bflo(pv[r][1]) * z[2] + bfhi(pv[r][1]) * z[3] + bflo(pv[r][2]) * z[4] + bfhi(pv[r][2]) * z[5];
            den += __shfl_xor_sync(0xffffffffu, den, 1);
            den += __shfl_xor_sync(0xffffffffu, den, 2);
            const float sc = gt[r] / (den + 1e-6f);
            const int tg = (rbase >> 3) + (r & 1) + (r >> 1) * 8;
            #pragma unroll
            for (int j = 0; j < 3; j++) {
                const int kb = fb + j;
                if (!(cslot && j == (odd ? 0 : 2)))
                    *(uint32_t*)(g_acat + (((kb >> 3) * 256 + tg) * 8 + (kb & 7)) * 128 + lane * 4) = packbf(bflo(pv[r][j]) * sc, bfhi(pv[r][j]) * sc);
            }
        }
    }
    PolyC pc;
    asm volatile("mov.b32 %0, 0x3F803F80;" : "=r"(pc.one));
    asm volatile("mov.b32 %0, 0xBFC0BFC0;" : "=r"(pc.cm15));
    pc.c3 = 0;
    asm volatile("mov.b32 %0, 0x42304230;" : "=r"(pc.c2));
    asm volatile("mov.b32 %0, 0xBF7CBF7C;" : "=r"(pc.c1));
    asm volatile("mov.b32 %0, 0x43744375;" : "=r"(pc.c0));

    #pragma unroll 1
    for (int tile = 0; tile < 2; tile++) {
        const int row0 = rbase + tile * 64;
        uint32_t q[8];
        q[0] = tile ? qv[2][0] : qv[0][0]; q[1] = tile ? qv[3][0] : qv[1][0];
        q[2] = tile ? qv[2][1] : qv[0][1]; q[3] = tile ? qv[3][1] : qv[1][1];
        q[4] = tile ? qv[2][2] : qv[0][2]; q[5] = tile ? qv[3][2] : qv[1][2];
        q[6] = 0; q[7] = 0;
        const float gt0 = tile ? gt[2] : gt[0], gt1 = tile ? gt[3] : gt[1];
        float n0 = bflo(q[0]) * bflo(q[0]) + bfhi(q[0]) * bfhi(q[0]) + bflo(q[2]) * bflo(q[2]) + bfhi(q[2]) * bfhi(q[2]) + bflo(q[4]) * bflo(q[4]) + bfhi(q[4]) * bfhi(q[4]);
        float n1 = bflo(q[1]) * bflo(q[1]) + bfhi(q[1]) * bfhi(q[1]) + bflo(q[3]) * bflo(q[3]) + bfhi(q[3]) * bfhi(q[3]) + bflo(q[5]) * bflo(q[5]) + bfhi(q[5]) * bfhi(q[5]);
        n0 += __shfl_xor_sync(0xffffffffu, n0, 1); n1 += __shfl_xor_sync(0xffffffffu, n1, 1);
        n0 += __shfl_xor_sync(0xffffffffu, n0, 2); n1 += __shfl_xor_sync(0xffffffffu, n1, 2);
        const float m0 = sqrtf(n0) * kmax * 1.02f + 0.0625f, m1 = sqrtf(n1) * kmax * 1.02f + 0.0625f;
        uint32_t unsafe = !(m0 <= 48.f && m1 <= 48.f);
        asm volatile("{.reg .pred p, q; setp.ne.u32 p, %0, 0; barrier.red.or.pred q, %1, 128, p; selp.u32 %0, 1, 0, q;}" : "+r"(unsafe) : "r"(wg + 1) : "memory");
        unsafe = __any_sync(0xffffffffu, unsafe);

        CK(1, 8 + tile * 3);
        float o[12];
        #pragma unroll
        for (int i = 0; i < 12; i++) o[i] = 0.f;
        fence_f(o);
        const uint64_t dk = mkdesc(sb, 128, 768, 0), dk2 = mkdesc(sb + 256, 0, 768, 0), dv = mkdesc(sb + 384, 768, 128, 0);
        float S[32];
        uint32_t p[16];
        if (!unsafe) {
            if (cslot) {
                const uint32_t c0 = (t & 1) ? 0x3B80u : ((packbf(-m0, 0.f) & 0xFFFFu) | 0x43FC0000u);
                const uint32_t c1 = (t & 1) ? 0x3B80u : ((packbf(-m1, 0.f) & 0xFFFFu) | 0x43FC0000u);
                if (odd) { q[0] = c0; q[1] = c1; } else { q[4] = c0; q[5] = c1; }
            }
            mbar_wait(bars, 0);
            WG_FENCE();
            wg_qk0(S, q[0], q[1], q[2], q[3], dk); wg_qk1(S, q[4], q[5], q[6], q[7], dk2);
            WG_COMMIT();
            WG_WAIT(0);
            fence_f(S);
            #pragma unroll 1
            for (int c = 0; c < 16; c++) {
                const uint32_t o0 = c * 768, o2 = ((c + 1) & 15) * 768;
                softmax_blk<0>(S, p, pc);
                fence_r(p);
                WG_FENCE();
                wg_qk0(S, q[0], q[1], q[2], q[3], dk + o0 + 384); wg_qk1(S, q[4], q[5], q[6], q[7], dk2 + o0 + 384);
                #pragma unroll
                for (int k = 0; k < 4; k++) wg_pv(o, p[4*k], p[4*k+1], p[4*k+2], p[4*k+3], dv + o0 + k * 96);
                WG_COMMIT();
                WG_WAIT(0);
                fence_f(S);
                softmax_blk<1>(S, p, pc);
                fence_r(p);
                mbar_wait(bars + 8 * ((c + 1) & 15), 0);
                WG_FENCE();
                wg_qk0(S, q[0], q[1], q[2], q[3], dk + o2); wg_qk1(S, q[4], q[5], q[6], q[7], dk2 + o2);
                #pragma unroll
                for (int k = 0; k < 4; k++) wg_pv(o, p[4*k], p[4*k+1], p[4*k+2], p[4*k+3], dv + o0 + 384 + k * 96);
                WG_COMMIT();
                WG_WAIT(0);
                fence_f(S);
            }
        } else {
            float rm0 = -INFINITY, rm1 = -INFINITY;
            #pragma unroll 1
            for (int b = 0; b < 32; b++) {
                if ((b & 1) == 0) mbar_wait(bars + 8 * (b >> 1), 0);
                WG_FENCE();
                wg_qk0(S, q[0], q[1], q[2], q[3], dk + b * 384); wg_qk1(S, q[4], q[5], q[6], q[7], dk2 + b * 384);
                WG_COMMIT();
                WG_WAIT(0);
                fence_f(S);
                float x0 = rm0, x1 = rm1;
                #pragma unroll
                for (int j = 0; j < 8; j++) { x0 = fmaxf(x0, fmaxf(S[4*j], S[4*j+1])); x1 = fmaxf(x1, fmaxf(S[4*j+2], S[4*j+3])); }
                x0 = fmaxf(x0, __shfl_xor_sync(0xffffffffu, x0, 1)); x1 = fmaxf(x1, __shfl_xor_sync(0xffffffffu, x1, 1));
                x0 = fmaxf(x0, __shfl_xor_sync(0xffffffffu, x0, 2)); x1 = fmaxf(x1, __shfl_xor_sync(0xffffffffu, x1, 2));
                const float c0 = ex2f(rm0 - x0), c1 = ex2f(rm1 - x1);
                rm0 = x0; rm1 = x1;
                #pragma unroll
                for (int j = 0; j < 3; j++) { o[4*j] *= c0; o[4*j+1] *= c0; o[4*j+2] *= c1; o[4*j+3] *= c1; }
                #pragma unroll
                for (int j = 0; j < 8; j++) {
                    p[2*j] = packbf(ex2f(S[4*j] - x0), ex2f(S[4*j+1] - x0));
                    p[2*j+1] = packbf(ex2f(S[4*j+2] - x1), ex2f(S[4*j+3] - x1));
                }
                fence_r(p); fence_f(o);
                WG_FENCE();
                #pragma unroll
                for (int k = 0; k < 4; k++) wg_pv(o, p[4*k], p[4*k+1], p[4*k+2], p[4*k+3], dv + b * 384 + k * 96);
                WG_COMMIT();
                WG_WAIT(0);
                fence_f(o);
            }
        }
        fence_f(o);
        CK(1, 9 + tile * 3);
        const int src = (lane & ~3) | (odd ? 0 : 2);
        const float l0 = __shfl_sync(0xffffffffu, odd ? o[0] : o[8], src), l1 = __shfl_sync(0xffffffffu, odd ? o[2] : o[10], src);
        const float s0 = (1.f - gt0) / l0, s1 = (1.f - gt1) / l1;
        #pragma unroll
        for (int j = 0; j < 3; j++) {
            const int kb = 80 + fb + j;
            uint8_t* dst = g_acat + (((kb >> 3) * 256 + (row0 >> 3)) * 8 + (kb & 7)) * 128 + lane * 4;
            if (!(cslot && j == (odd ? 0 : 2))) {
                *(uint32_t*)dst = packbf(o[4*j] * s0, o[4*j+1] * s0);
                *(uint32_t*)(dst + 1024) = packbf(o[4*j+2] * s1, o[4*j+3] * s1);
            }
        }
    }
    TS_MAX(7);
}

__constant__ uint8_t k3_map[130] = {0,1,2,3,16,17,18,19,32,33,34,35,48,49,50,51,4,5,6,7,20,21,22,23,36,37,38,39,52,53,54,55,8,9,24,25,40,41,56,57,64,65,66,67,80,81,82,83,96,97,98,99,112,113,114,115,68,69,70,71,84,85,86,87,100,101,102,103,116,117,118,119,72,73,88,89,104,105,120,121,128,129,130,131,144,145,146,147,160,161,162,163,176,177,178,179,132,133,134,135,148,149,150,151,164,165,166,167,180,181,182,183,136,137,152,153,168,169,184,185,192,193,194,195,196,197,198,199,200,201};
#define K3_STAGE 28672
#define K3_NST 6
#define K3_SMEM (K3_NST * K3_STAGE + 1024)
__global__ void __launch_bounds__(288, 1)
out_kernel(const __grid_constant__ CUtensorMap tm_wm, const __grid_constant__ CUtensorMap tm_wob,
           __nv_bfloat16* __restrict__ out) {
    extern __shared__ __align__(1024) uint8_t smem[];
    const uint32_t sb = smem_u32(smem);
    const uint32_t bar_full = sb + K3_NST * K3_STAGE, bar_empty = bar_full + 64;
    const int tid = threadIdx.x, warp = tid >> 5, lane = tid & 31;
    const int tt = k3_map[blockIdx.x] >> 4, ct = k3_map[blockIdx.x] & 15;
    if (tid == 0) {
        for (int i = 0; i < K3_NST; i++) { mbar_init(bar_full + 8 * i, 1); mbar_init(bar_empty + 8 * i, 8); }
        asm volatile("fence.mbarrier_init.release.cluster;" ::: "memory");
    }
    __syncthreads();
    CK3(0);
    if (warp == 8) {
        if (lane == 0) {
            TS_MIN(8);
            GRIDDEP_WAIT();
            TS_MIN(9); TS_MAX(18); CK3(1);
            for (int it = 0; it < 20; it++) {
                const int s = it % K3_NST;
                if (it >= K3_NST) mbar_wait(bar_empty + 8 * s, ((it / K3_NST) - 1) & 1);
                const uint32_t st = sb + s * K3_STAGE, fb = bar_full + 8 * s;
                mbar_expect(fb, K3_STAGE);
                tma2d(st, it < 10 ? &tm_wm : &tm_wob, fb, ct * 64, (it % 10) * 64);
                bulk_load(st + 8192, g_acat + (size_t)(it * 256 + tt * 20) * 1024, 20480, fb);
            }
        }
    } else {
        const int wg = __shfl_sync(0xffffffffu, warp >> 2, 0), w4 = warp & 3;
        float acc[40];
        for (int it = 0; it < 20; it++) {
            const int s = it % K3_NST;
            mbar_wait(bar_full + 8 * s, (it / K3_NST) & 1);
            if (it == 0) CK3(2); if (it == 6) CK3(3); if (it == 12) CK3(4);
            const uint32_t st = sb + s * K3_STAGE;
            const uint64_t da = mkdesc(st, 8192, 1024, 1), db = mkdesc(st + 8192 + wg * 10240, 128, 1024, 0);
            WG_FENCE();
            #pragma unroll
            for (int k = 0; k < 4; k++) wg_ss_n80_at(acc, da + k * 128, db + k * 16, (it | k) != 0);
            WG_COMMIT();
            WG_WAIT(0);
            if (lane == 0) mbar_arrive(bar_empty + 8 * s);
        }
        fence_f(acc);
        CK3(5);
        named_bar(1, 256);
        const uint32_t tb = sb + wg * 10240;
        #pragma unroll
        for (int j = 0; j < 10; j += 2) {
            const int tok = 8 * (j + (lane >> 4)) + (lane & 7);
            const int chunk = (2 * w4 + ((lane >> 3) & 1)) ^ (tok & 7);
            const uint32_t addr = tb + tok * 128 + chunk * 16;
            asm volatile("stmatrix.sync.aligned.m8n8.x4.trans.shared.b16 [%0], {%1,%2,%3,%4};" :: "r"(addr),
                "r"(packbf(acc[4*j], acc[4*j+1])), "r"(packbf(acc[4*j+2], acc[4*j+3])), "r"(packbf(acc[4*j+4], acc[4*j+5])), "r"(packbf(acc[4*j+6], acc[4*j+7])) : "memory");
        }
        named_bar(2 + wg, 128);
        const int lt = tid & 127;
        #pragma unroll
        for (int i = 0; i < 5; i++) {
            const int idx = lt + 128 * i, tok = idx >> 3, ch = idx & 7;
            const int gtok = tt * 160 + wg * 80 + tok;
            const uint4 v = *(const uint4*)(smem + wg * 10240 + tok * 128 + ((ch ^ (tok & 7)) * 16));
            if (gtok < SEQ) *(uint4*)(out + (size_t)gtok * DM + ct * 64 + ch * 8) = v;
        }
        TS_MAX(10); CK3(6);
    }
}

typedef CUresult (*PFN_tmapEncode)(CUtensorMap*, CUtensorMapDataType, cuuint32_t, void*, const cuuint64_t*, const cuuint64_t*, const cuuint32_t*, const cuuint32_t*,
                                   CUtensorMapInterleave, CUtensorMapSwizzle, CUtensorMapL2promotion, CUtensorMapFloatOOBfill);
static void make_map(PFN_tmapEncode enc, CUtensorMap* tm, const void* ptr, uint64_t cols, uint64_t rows, uint32_t bcols, uint32_t brows) {
    cuuint64_t gd[2] = {cols, rows}; cuuint64_t gs[1] = {cols * 2}; cuuint32_t bx[2] = {bcols, brows}; cuuint32_t es[2] = {1, 1};
    enc(tm, CU_TENSOR_MAP_DATA_TYPE_BFLOAT16, 2, (void*)ptr, gd, gs, bx, es, CU_TENSOR_MAP_INTERLEAVE_NONE, CU_TENSOR_MAP_SWIZZLE_128B,
        CU_TENSOR_MAP_L2_PROMOTION_L2_128B, CU_TENSOR_MAP_FLOAT_OOB_FILL_NONE);
}

extern "C" void kernel_launch(void* const* d_in, const int* in_sizes, int n_in, void* d_out, int out_size) {
    const __nv_bfloat16* x = (const __nv_bfloat16*)d_in[0];
    const __nv_bfloat16* a_wqkv = (const __nv_bfloat16*)d_in[1];
    const __nv_bfloat16* a_wo = (const __nv_bfloat16*)d_in[2];
    const __nv_bfloat16* b_wqkv = (const __nv_bfloat16*)d_in[4];
    const __nv_bfloat16* b_wo = (const __nv_bfloat16*)d_in[5];
    const __nv_bfloat16* gate_w = (const __nv_bfloat16*)d_in[6];
    static CUtensorMap tm_x, tm_wm, tm_wob;
    static WMaps tm_w;
    static const void* cached[4] = {nullptr, nullptr, nullptr, nullptr};
    if (cached[0] != x || cached[1] != a_wqkv || cached[2] != b_wqkv || cached[3] != b_wo) {
        void* fn = nullptr; cudaDriverEntryPointQueryResult qr;
        cudaGetDriverEntryPoint("cuTensorMapEncodeTiled", &fn, cudaEnableDefault, &qr);
        PFN_tmapEncode enc = (PFN_tmapEncode)fn;
        void* p_wm;
        cudaGetSymbolAddress(&p_wm, g_wm);
        make_map(enc, &tm_x, x, DM, SEQ, 64, 128);
        for (int i = 0; i < 4; i++) {
            cuuint64_t gd[4] = {64, DM, 10, 3}; cuuint64_t gs[3] = {3 * DM * 2, 128, DM * 2};
            cuuint32_t bx[4] = {64, 64, 3, (cuuint32_t)((i & 1) ? 1 : 2)}; cuuint32_t es[4] = {1, 1, 1, 1};
            enc(&tm_w.m[i], CU_TENSOR_MAP_DATA_TYPE_BFLOAT16, 4, (void*)(i < 2 ? a_wqkv : b_wqkv), gd, gs, bx, es, CU_TENSOR_MAP_INTERLEAVE_NONE,
                CU_TENSOR_MAP_SWIZZLE_128B, CU_TENSOR_MAP_L2_PROMOTION_L2_128B, CU_TENSOR_MAP_FLOAT_OOB_FILL_NONE);
        }
        make_map(enc, &tm_wm, p_wm, DM, DM, 64, 64);
        make_map(enc, &tm_wob, b_wo, DM, DM, 64, 64);
        cudaFuncSetAttribute(qkv_kernel, cudaFuncAttributeMaxDynamicSharedMemorySize, K1_SMEM);
        cudaFuncSetAttribute(attn_kernel, cudaFuncAttributeMaxDynamicSharedMemorySize, K2_SMEM);
        cudaFuncSetAttribute(out_kernel, cudaFuncAttributeMaxDynamicSharedMemorySize, K3_SMEM);
        cached[0] = x; cached[1] = a_wqkv; cached[2] = b_wqkv; cached[3] = b_wo;
    }
    cudaStream_t st = cudaStreamPerThread;
    cudaLaunchAttribute at[1];
    at[0].id = cudaLaunchAttributeProgrammaticStreamSerialization; at[0].val.programmaticStreamSerializationAllowed = 1;
    cudaLaunchConfig_t cfg = {};
    cfg.stream = st;
    cfg.gridDim = dim3(128); cfg.blockDim = dim3(512); cfg.dynamicSmemBytes = K1_SMEM; cfg.attrs = at; cfg.numAttrs = 0;
    cudaLaunchKernelEx(&cfg, qkv_kernel, tm_x, tm_w, x, gate_w, a_wo, b_wo);
    cfg.gridDim = dim3(132); cfg.blockDim = dim3(512); cfg.dynamicSmemBytes = K2_SMEM; cfg.numAttrs = 1;
    cudaLaunchKernelEx(&cfg, attn_kernel, a_wo);
    cfg.gridDim = dim3(130); cfg.blockDim = dim3(288); cfg.dynamicSmemBytes = K3_SMEM; cfg.numAttrs = 1;
    cudaLaunchKernelEx(&cfg, out_kernel, tm_wm, tm_wob, (__nv_bfloat16*)d_out);
}
```

```cpp
#include <cuda_runtime.h>
#include <cuda_bf16.h>
#include <cuda.h>
#include <stdint.h>

#define SEQ 2048
#define DM 640
#define NH 32
#define DH 20

#define POLY_MASK 0xD5DDu
#define POLY_DEG 1

__device__ __align__(1024) uint8_t g_kvimg[NH * 196608];
__device__ __align__(1024) uint8_t g_qb[SEQ * DM * 2];
__device__ __align__(1024) uint8_t g_pq[SEQ * DM * 2];
__device__ __align__(1024) uint8_t g_acat[SEQ * 2 * DM * 2 + 4096];
__device__ __align__(1024) __nv_bfloat16 g_wm[DM * DM];
__device__ __align__(16) float g_kvpart[16 * NH * 480];
__device__ __align__(16) float g_zpart[16 * NH * 20];
__device__ __align__(16) float g_kn2[NH * 128];
__device__ __align__(16) float g_gate[SEQ];

__device__ __forceinline__ uint32_t smem_u32(const void* p) { return (uint32_t)__cvta_generic_to_shared(p); }
__device__ __forceinline__ uint64_t mkdesc(uint32_t saddr, uint32_t lbo, uint32_t sbo, uint32_t swz) {
    return (uint64_t)((saddr & 0x3FFFF) >> 4) | ((uint64_t)(lbo >> 4) << 16) | ((uint64_t)(sbo >> 4) << 32) | ((uint64_t)swz << 62);
}
#define WG_FENCE() asm volatile("wgmma.fence.sync.aligned;" ::: "memory")
#define WG_COMMIT() asm volatile("wgmma.commit_group.sync.aligned;" ::: "memory")
#define WG_WAIT(n) asm volatile("wgmma.wait_group.sync.aligned %0;" :: "n"(n) : "memory")
template<int N> __device__ __forceinline__ void fence_f(float (&d)[N]) {
    #pragma unroll
    for (int i = 0; i < N; i++) asm volatile("" : "+f"(d[i]) :: "memory");
}
template<int N> __device__ __forceinline__ void fence_r(uint32_t (&d)[N]) {
    #pragma unroll
    for (int i = 0; i < N; i++) asm volatile("" : "+r"(d[i]) :: "memory");
}
__device__ __forceinline__ void mbar_init(uint32_t bar, uint32_t cnt) { asm volatile("mbarrier.init.shared::cta.b64 [%0], %1;" :: "r"(bar), "r"(cnt)); }
__device__ __forceinline__ void mbar_expect(uint32_t bar, uint32_t bytes) { asm volatile("mbarrier.arrive.expect_tx.shared::cta.b64 _, [%0], %1;" :: "r"(bar), "r"(bytes) : "memory"); }
__device__ __forceinline__ void mbar_arrive(uint32_t bar) { asm volatile("mbarrier.arrive.shared::cta.b64 _, [%0];" :: "r"(bar) : "memory"); }
__device__ __forceinline__ void mbar_wait(uint32_t bar, uint32_t parity) {
    asm volatile("{\n.reg .pred p;\nWAIT_%=:\nmbarrier.try_wait.parity.shared::cta.b64 p, [%0], %1;\n@p bra DONE_%=;\nbra WAIT_%=;\nDONE_%=:\n}" :: "r"(bar), "r"(parity) : "memory");
}
__device__ __forceinline__ void tma2d(uint32_t dst, const CUtensorMap* tm, uint32_t bar, int c0, int c1) {
    asm volatile("cp.async.bulk.tensor.2d.shared::cluster.global.mbarrier::complete_tx::bytes [%0], [%1, {%3,%4}], [%2];"
        :: "r"(dst), "l"((uint64_t)tm), "r"(bar), "r"(c0), "r"(c1) : "memory");
}
__device__ __forceinline__ void bulk_load(uint32_t dst, const void* src, uint32_t bytes, uint32_t bar) {
    asm volatile("cp.async.bulk.shared::cluster.global.mbarrier::complete_tx::bytes [%0], [%1], %2, [%3];" :: "r"(dst), "l"(src), "r"(bytes), "r"(bar) : "memory");
}
__device__ __forceinline__ void l2_prefetch(const void* src, uint32_t bytes) {
    asm volatile("cp.async.bulk.prefetch.L2.global [%0], %1;" :: "l"(src), "r"(bytes) : "memory");
}
__device__ __forceinline__ void named_bar(int id, int n) { asm volatile("bar.sync %0, %1;" :: "r"(id), "r"(n) : "memory"); }
__device__ __forceinline__ float ex2f(float x) { float y; asm("ex2.approx.ftz.f32 %0, %1;" : "=f"(y) : "f"(x)); return y; }
__device__ __forceinline__ uint32_t packbf(float lo, float hi) { uint32_t r; asm("cvt.rn.bf16x2.f32 %0, %1, %2;" : "=r"(r) : "f"(hi), "f"(lo)); return r; }
__device__ __forceinline__ float bflo(uint32_t v) { return __uint_as_float(v << 16); }
__device__ __forceinline__ float bfhi(uint32_t v) { return __uint_as_float(v & 0xFFFF0000u); }
__device__ __forceinline__ float phi_f(float t) { return (fmaxf(t, 0.f) + 1e-6f) + ex2f(fminf(t, 0.f) * 1.4426950408889634f); }
__device__ __forceinline__ uint32_t q_off(int tok, int col) { return ((tok >> 3) * 80 + (col >> 3)) * 128 + (tok & 7) * 16 + (col & 7) * 2; }
__device__ __forceinline__ uint32_t acat_off(int tok, int kk) { return (((kk >> 6) * 256 + (tok >> 3)) * 8 + ((kk >> 3) & 7)) * 128 + (tok & 7) * 16 + (kk & 7) * 2; }
#define GRIDDEP_WAIT() asm volatile("griddepcontrol.wait;" ::: "memory")
#define GRIDDEP_LAUNCH() asm volatile("griddepcontrol.launch_dependents;" ::: "memory")

#define TS_MIN(i)
#define CK(k, i)
#define CK3(i)
#define TS_MAX(i)

__device__ __forceinline__ void wg_rs_n128_bt(float (&d)[64], uint32_t a0, uint32_t a1, uint32_t a2, uint32_t a3, uint64_t db) {
    asm volatile("wgmma.mma_async.sync.aligned.m64n128k16.f32.bf16.bf16 {%0,%1,%2,%3,%4,%5,%6,%7,%8,%9,%10,%11,%12,%13,%14,%15,%16,%17,%18,%19,%20,%21,%22,%23,%24,%25,%26,%27,%28,%29,%30,%31,%32,%33,%34,%35,%36,%37,%38,%39,%40,%41,%42,%43,%44,%45,%46,%47,%48,%49,%50,%51,%52,%53,%54,%55,%56,%57,%58,%59,%60,%61,%62,%63}, {%64,%65,%66,%67}, %68, 1, 1, 1, 1;"
      : "+f"(d[0]),"+f"(d[1]),"+f"(d[2]),"+f"(d[3]),"+f"(d[4]),"+f"(d[5]),"+f"(d[6]),"+f"(d[7]),"+f"(d[8]),"+f"(d[9]),"+f"(d[10]),"+f"(d[11]),"+f"(d[12]),"+f"(d[13]),"+f"(d[14]),"+f"(d[15]),"+f"(d[16]),"+f"(d[17]),"+f"(d[18]),"+f"(d[19]),"+f"(d[20]),"+f"(d[21]),"+f"(d[22]),"+f"(d[23]),"+f"(d[24]),"+f"(d[25]),"+f"(d[26]),"+f"(d[27]),"+f"(d[28]),"+f"(d[29]),"+f"(d[30]),"+f"(d[31]),"+f"(d[32]),"+f"(d[33]),"+f"(d[34]),"+f"(d[35]),"+f"(d[36]),"+f"(d[37]),"+f"(d[38]),"+f"(d[39]),"+f"(d[40]),"+f"(d[41]),"+f"(d[42]),"+f"(d[43]),"+f"(d[44]),"+f"(d[45]),"+f"(d[46]),"+f"(d[47]),"+f"(d[48]),"+f"(d[49]),"+f"(d[50]),"+f"(d[51]),"+f"(d[52]),"+f"(d[53]),"+f"(d[54]),"+f"(d[55]),"+f"(d[56]),"+f"(d[57]),"+f"(d[58]),"+f"(d[59]),"+f"(d[60]),"+f"(d[61]),"+f"(d[62]),"+f"(d[63]) : "r"(a0), "r"(a1), "r"(a2), "r"(a3), "l"(db));
}
__device__ __forceinline__ void wg_ss_n64_bt(float (&d)[32], uint64_t da, uint64_t db, int acc) {
    asm volatile("{.reg .pred p; setp.ne.b32 p, %34, 0;\n"
      "wgmma.mma_async.sync.aligned.m64n64k16.f32.bf16.bf16 {%0,%1,%2,%3,%4,%5,%6,%7,%8,%9,%10,%11,%12,%13,%14,%15,%16,%17,%18,%19,%20,%21,%22,%23,%24,%25,%26,%27,%28,%29,%30,%31}, %32, %33, p, 1, 1, 0, 1;}"
      : "+f"(d[0]),"+f"(d[1]),"+f"(d[2]),"+f"(d[3]),"+f"(d[4]),"+f"(d[5]),"+f"(d[6]),"+f"(d[7]),"+f"(d[8]),"+f"(d[9]),"+f"(d[10]),"+f"(d[11]),"+f"(d[12]),"+f"(d[13]),"+f"(d[14]),"+f"(d[15]),"+f"(d[16]),"+f"(d[17]),"+f"(d[18]),"+f"(d[19]),"+f"(d[20]),"+f"(d[21]),"+f"(d[22]),"+f"(d[23]),"+f"(d[24]),"+f"(d[25]),"+f"(d[26]),"+f"(d[27]),"+f"(d[28]),"+f"(d[29]),"+f"(d[30]),"+f"(d[31]) : "l"(da), "l"(db), "r"(acc));
}
__device__ __forceinline__ void wg_ss_n32_bt(float (&d)[16], uint64_t da, uint64_t db, int acc) {
    asm volatile("{.reg .pred p; setp.ne.b32 p, %18, 0;\n"
      "wgmma.mma_async.sync.aligned.m64n32k16.f32.bf16.bf16 {%0,%1,%2,%3,%4,%5,%6,%7,%8,%9,%10,%11,%12,%13,%14,%15}, %16, %17, p, 1, 1, 0, 1;}"
      : "+f"(d[0]),"+f"(d[1]),"+f"(d[2]),"+f"(d[3]),"+f"(d[4]),"+f"(d[5]),"+f"(d[6]),"+f"(d[7]),"+f"(d[8]),"+f"(d[9]),"+f"(d[10]),"+f"(d[11]),"+f"(d[12]),"+f"(d[13]),"+f"(d[14]),"+f"(d[15]) : "l"(da), "l"(db), "r"(acc));
}
__device__ __forceinline__ void wg_rs_n32_bt(float (&d)[16], uint32_t a0, uint32_t a1, uint32_t a2, uint32_t a3, uint64_t db) {
    asm volatile("wgmma.mma_async.sync.aligned.m64n32k16.f32.bf16.bf16 {%0,%1,%2,%3,%4,%5,%6,%7,%8,%9,%10,%11,%12,%13,%14,%15}, {%16,%17,%18,%19}, %20, 1, 1, 1, 1;"
      : "+f"(d[0]),"+f"(d[1]),"+f"(d[2]),"+f"(d[3]),"+f"(d[4]),"+f"(d[5]),"+f"(d[6]),"+f"(d[7]),"+f"(d[8]),"+f"(d[9]),"+f"(d[10]),"+f"(d[11]),"+f"(d[12]),"+f"(d[13]),"+f"(d[14]),"+f"(d[15]) : "r"(a0), "r"(a1), "r"(a2), "r"(a3), "l"(db));
}
__device__ __forceinline__ void wg_ss_n88_atbt(float (&d)[44], uint64_t da, uint64_t db, int acc) {
    asm volatile("{.reg .pred p; setp.ne.b32 p, %46, 0;\n"
      "wgmma.mma_async.sync.aligned.m64n88k16.f32.bf16.bf16 {%0,%1,%2,%3,%4,%5,%6,%7,%8,%9,%10,%11,%12,%13,%14,%15,%16,%17,%18,%19,%20,%21,%22,%23,%24,%25,%26,%27,%28,%29,%30,%31,%32,%33,%34,%35,%36,%37,%38,%39,%40,%41,%42,%43}, %44, %45, p, 1, 1, 1, 1;}"
      : "+f"(d[0]),"+f"(d[1]),"+f"(d[2]),"+f"(d[3]),"+f"(d[4]),"+f"(d[5]),"+f"(d[6]),"+f"(d[7]),"+f"(d[8]),"+f"(d[9]),"+f"(d[10]),"+f"(d[11]),"+f"(d[12]),"+f"(d[13]),"+f"(d[14]),"+f"(d[15]),"+f"(d[16]),"+f"(d[17]),"+f"(d[18]),"+f"(d[19]),"+f"(d[20]),"+f"(d[21]),"+f"(d[22]),"+f"(d[23]),"+f"(d[24]),"+f"(d[25]),"+f"(d[26]),"+f"(d[27]),"+f"(d[28]),"+f"(d[29]),"+f"(d[30]),"+f"(d[31]),"+f"(d[32]),"+f"(d[33]),"+f"(d[34]),"+f"(d[35]),"+f"(d[36]),"+f"(d[37]),"+f"(d[38]),"+f"(d[39]),"+f"(d[40]),"+f"(d[41]),"+f"(d[42]),"+f"(d[43]) : "l"(da), "l"(db), "r"(acc));
}
__device__ __forceinline__ void wg_ss_n8_atbt(float (&d)[4], uint64_t da, uint64_t db, int acc) {
    asm volatile("{.reg .pred p; setp.ne.b32 p, %6, 0;\n"
      "wgmma.mma_async.sync.aligned.m64n8k16.f32.bf16.bf16 {%0,%1,%2,%3}, %4, %5, p, 1, 1, 1, 1;}"
      : "+f"(d[0]),"+f"(d[1]),"+f"(d[2]),"+f"(d[3]) : "l"(da), "l"(db), "r"(acc));
}
__device__ __forceinline__ void wg_ss_n160_at(float (&d)[80], uint64_t da, uint64_t db, int acc) {
    asm volatile("{.reg .pred p; setp.ne.b32 p, %82, 0;\n"
      "wgmma.mma_async.sync.aligned.m64n160k16.f32.bf16.bf16 {%0,%1,%2,%3,%4,%5,%6,%7,%8,%9,%10,%11,%12,%13,%14,%15,%16,%17,%18,%19,%20,%21,%22,%23,%24,%25,%26,%27,%28,%29,%30,%31,%32,%33,%34,%35,%36,%37,%38,%39,%40,%41,%42,%43,%44,%45,%46,%47,%48,%49,%50,%51,%52,%53,%54,%55,%56,%57,%58,%59,%60,%61,%62,%63,%64,%65,%66,%67,%68,%69,%70,%71,%72,%73,%74,%75,%76,%77,%78,%79}, %80, %81, p, 1, 1, 1, 0;}"
      : "+f"(d[0]),"+f"(d[1]),"+f"(d[2]),"+f"(d[3]),"+f"(d[4]),"+f"(d[5]),"+f"(d[6]),"+f"(d[7]),"+f"(d[8]),"+f"(d[9]),"+f"(d[10]),"+f"(d[11]),"+f"(d[12]),"+f"(d[13]),"+f"(d[14]),"+f"(d[15]),"+f"(d[16]),"+f"(d[17]),"+f"(d[18]),"+f"(d[19]),"+f"(d[20]),"+f"(d[21]),"+f"(d[22]),"+f"(d[23]),"+f"(d[24]),"+f"(d[25]),"+f"(d[26]),"+f"(d[27]),"+f"(d[28]),"+f"(d[29]),"+f"(d[30]),"+f"(d[31]),"+f"(d[32]),"+f"(d[33]),"+f"(d[34]),"+f"(d[35]),"+f"(d[36]),"+f"(d[37]),"+f"(d[38]),"+f"(d[39]),"+f"(d[40]),"+f"(d[41]),"+f"(d[42]),"+f"(d[43]),"+f"(d[44]),"+f"(d[45]),"+f"(d[46]),"+f"(d[47]),"+f"(d[48]),"+f"(d[49]),"+f"(d[50]),"+f"(d[51]),"+f"(d[52]),"+f"(d[53]),"+f"(d[54]),"+f"(d[55]),"+f"(d[56]),"+f"(d[57]),"+f"(d[58]),"+f"(d[59]),"+f"(d[60]),"+f"(d[61]),"+f"(d[62]),"+f"(d[63]),"+f"(d[64]),"+f"(d[65]),"+f"(d[66]),"+f"(d[67]),"+f"(d[68]),"+f"(d[69]),"+f"(d[70]),"+f"(d[71]),"+f"(d[72]),"+f"(d[73]),"+f"(d[74]),"+f"(d[75]),"+f"(d[76]),"+f"(d[77]),"+f"(d[78]),"+f"(d[79]) : "l"(da), "l"(db), "r"(acc));
}
__device__ __forceinline__ void wg_qk0(float (&d)[32], uint32_t a0, uint32_t a1, uint32_t a2, uint32_t a3, uint64_t db) {
    asm volatile("wgmma.mma_async.sync.aligned.m64n64k16.f32.bf16.bf16 {%0,%1,%2,%3,%4,%5,%6,%7,%8,%9,%10,%11,%12,%13,%14,%15,%16,%17,%18,%19,%20,%21,%22,%23,%24,%25,%26,%27,%28,%29,%30,%31}, {%32,%33,%34,%35}, %36, 0, 1, 1, 0;"
      : "+f"(d[0]),"+f"(d[1]),"+f"(d[2]),"+f"(d[3]),"+f"(d[4]),"+f"(d[5]),"+f"(d[6]),"+f"(d[7]),"+f"(d[8]),"+f"(d[9]),"+f"(d[10]),"+f"(d[11]),"+f"(d[12]),"+f"(d[13]),"+f"(d[14]),"+f"(d[15]),"+f"(d[16]),"+f"(d[17]),"+f"(d[18]),"+f"(d[19]),"+f"(d[20]),"+f"(d[21]),"+f"(d[22]),"+f"(d[23]),"+f"(d[24]),"+f"(d[25]),"+f"(d[26]),"+f"(d[27]),"+f"(d[28]),"+f"(d[29]),"+f"(d[30]),"+f"(d[31]) : "r"(a0), "r"(a1), "r"(a2), "r"(a3), "l"(db));
}
__device__ __forceinline__ void wg_qk1(float (&d)[32], uint32_t a0, uint32_t a1, uint32_t a2, uint32_t a3, uint64_t db) {
    asm volatile("wgmma.mma_async.sync.aligned.m64n64k16.f32.bf16.bf16 {%0,%1,%2,%3,%4,%5,%6,%7,%8,%9,%10,%11,%12,%13,%14,%15,%16,%17,%18,%19,%20,%21,%22,%23,%24,%25,%26,%27,%28,%29,%30,%31}, {%32,%33,%34,%35}, %36, 1, 1, 1, 0;"
      : "+f"(d[0]),"+f"(d[1]),"+f"(d[2]),"+f"(d[3]),"+f"(d[4]),"+f"(d[5]),"+f"(d[6]),"+f"(d[7]),"+f"(d[8]),"+f"(d[9]),"+f"(d[10]),"+f"(d[11]),"+f"(d[12]),"+f"(d[13]),"+f"(d[14]),"+f"(d[15]),"+f"(d[16]),"+f"(d[17]),"+f"(d[18]),"+f"(d[19]),"+f"(d[20]),"+f"(d[21]),"+f"(d[22]),"+f"(d[23]),"+f"(d[24]),"+f"(d[25]),"+f"(d[26]),"+f"(d[27]),"+f"(d[28]),"+f"(d[29]),"+f"(d[30]),"+f"(d[31]) : "r"(a0), "r"(a1), "r"(a2), "r"(a3), "l"(db));
}
__device__ __forceinline__ void wg_qk0w(float (&d)[64], uint32_t a0, uint32_t a1, uint32_t a2, uint32_t a3, uint64_t db) {
    asm volatile("wgmma.mma_async.sync.aligned.m64n128k16.f32.bf16.bf16 {%0,%1,%2,%3,%4,%5,%6,%7,%8,%9,%10,%11,%12,%13,%14,%15,%16,%17,%18,%19,%20,%21,%22,%23,%24,%25,%26,%27,%28,%29,%30,%31,%32,%33,%34,%35,%36,%37,%38,%39,%40,%41,%42,%43,%44,%45,%46,%47,%48,%49,%50,%51,%52,%53,%54,%55,%56,%57,%58,%59,%60,%61,%62,%63}, {%64,%65,%66,%67}, %68, 0, 1, 1, 0;"
      : "+f"(d[0]),"+f"(d[1]),"+f"(d[2]),"+f"(d[3]),"+f"(d[4]),"+f"(d[5]),"+f"(d[6]),"+f"(d[7]),"+f"(d[8]),"+f"(d[9]),"+f"(d[10]),"+f"(d[11]),"+f"(d[12]),"+f"(d[13]),"+f"(d[14]),"+f"(d[15]),"+f"(d[16]),"+f"(d[17]),"+f"(d[18]),"+f"(d[19]),"+f"(d[20]),"+f"(d[21]),"+f"(d[22]),"+f"(d[23]),"+f"(d[24]),"+f"(d[25]),"+f"(d[26]),"+f"(d[27]),"+f"(d[28]),"+f"(d[29]),"+f"(d[30]),"+f"(d[31]),"+f"(d[32]),"+f"(d[33]),"+f"(d[34]),"+f"(d[35]),"+f"(d[36]),"+f"(d[37]),"+f"(d[38]),"+f"(d[39]),"+f"(d[40]),"+f"(d[41]),"+f"(d[42]),"+f"(d[43]),"+f"(d[44]),"+f"(d[45]),"+f"(d[46]),"+f"(d[47]),"+f"(d[48]),"+f"(d[49]),"+f"(d[50]),"+f"(d[51]),"+f"(d[52]),"+f"(d[53]),"+f"(d[54]),"+f"(d[55]),"+f"(d[56]),"+f"(d[57]),"+f"(d[58]),"+f"(d[59]),"+f"(d[60]),"+f"(d[61]),"+f"(d[62]),"+f"(d[63]) : "r"(a0), "r"(a1), "r"(a2), "r"(a3), "l"(db));
}
__device__ __forceinline__ void wg_qk1w(float (&d)[64], uint32_t a0, uint32_t a1, uint32_t a2, uint32_t a3, uint64_t db) {
    asm volatile("wgmma.mma_async.sync.aligned.m64n128k16.f32.bf16.bf16 {%0,%1,%2,%3,%4,%5,%6,%7,%8,%9,%10,%11,%12,%13,%14,%15,%16,%17,%18,%19,%20,%21,%22,%23,%24,%25,%26,%27,%28,%29,%30,%31,%32,%33,%34,%35,%36,%37,%38,%39,%40,%41,%42,%43,%44,%45,%46,%47,%48,%49,%50,%51,%52,%53,%54,%55,%56,%57,%58,%59,%60,%61,%62,%63}, {%64,%65,%66,%67}, %68, 1, 1, 1, 0;"
      : "+f"(d[0]),"+f"(d[1]),"+f"(d[2]),"+f"(d[3]),"+f"(d[4]),"+f"(d[5]),"+f"(d[6]),"+f"(d[7]),"+f"(d[8]),"+f"(d[9]),"+f"(d[10]),"+f"(d[11]),"+f"(d[12]),"+f"(d[13]),"+f"(d[14]),"+f"(d[15]),"+f"(d[16]),"+f"(d[17]),"+f"(d[18]),"+f"(d[19]),"+f"(d[20]),"+f"(d[21]),"+f"(d[22]),"+f"(d[23]),"+f"(d[24]),"+f"(d[25]),"+f"(d[26]),"+f"(d[27]),"+f"(d[28]),"+f"(d[29]),"+f"(d[30]),"+f"(d[31]),"+f"(d[32]),"+f"(d[33]),"+f"(d[34]),"+f"(d[35]),"+f"(d[36]),"+f"(d[37]),"+f"(d[38]),"+f"(d[39]),"+f"(d[40]),"+f"(d[41]),"+f"(d[42]),"+f"(d[43]),"+f"(d[44]),"+f"(d[45]),"+f"(d[46]),"+f"(d[47]),"+f"(d[48]),"+f"(d[49]),"+f"(d[50]),"+f"(d[51]),"+f"(d[52]),"+f"(d[53]),"+f"(d[54]),"+f"(d[55]),"+f"(d[56]),"+f"(d[57]),"+f"(d[58]),"+f"(d[59]),"+f"(d[60]),"+f"(d[61]),"+f"(d[62]),"+f"(d[63]) : "r"(a0), "r"(a1), "r"(a2), "r"(a3), "l"(db));
}
__device__ __forceinline__ void wg_pv(float (&d)[12], uint32_t a0, uint32_t a1, uint32_t a2, uint32_t a3, uint64_t db) {
    asm volatile("wgmma.mma_async.sync.aligned.m64n24k16.f32.bf16.bf16 {%0,%1,%2,%3,%4,%5,%6,%7,%8,%9,%10,%11}, {%12,%13,%14,%15}, %16, 1, 1, 1, 1;"
      : "+f"(d[0]),"+f"(d[1]),"+f"(d[2]),"+f"(d[3]),"+f"(d[4]),"+f"(d[5]),"+f"(d[6]),"+f"(d[7]),"+f"(d[8]),"+f"(d[9]),"+f"(d[10]),"+f"(d[11]) : "r"(a0), "r"(a1), "r"(a2), "r"(a3), "l"(db));
}

#define K1_ONES 204800
#define K1_BARS 205056
#define K1_SMEM 205312
#define QSCALE 0.32259799f
#define K1_BAR(i) (sb + K1_BARS + 8 * (i))

__device__ __forceinline__ void tma4d(uint32_t dst, const CUtensorMap* tm, uint32_t bar, int c0, int c1, int c2, int c3) {
    asm volatile("cp.async.bulk.tensor.4d.shared::cluster.global.mbarrier::complete_tx::bytes [%0], [%1, {%3,%4,%5,%6}], [%2];"
        :: "r"(dst), "l"((uint64_t)tm), "r"(bar), "r"(c0), "r"(c1), "r"(c2), "r"(c3) : "memory");
}
__device__ __forceinline__ void k1_issue(int pass, int kb, uint32_t sb, const CUtensorMap* tx, const CUtensorMap* tw, int mt, int hg) {
    const int s = pass ? kb % 5 : kb % 3;
    const uint32_t st = sb + (pass ? s * 40960 : s * 65536), fb = K1_BAR(pass ? s : 10 + s);
    mbar_expect(fb, pass ? 40960 : 65536);
    tma2d(st, tx, fb, kb * 64, mt * 128);
    tma4d(st + 16384, tw + pass, fb, 0, kb * 64, (hg * 160) >> 6, 1 - pass);
}
__device__ __forceinline__ void stsm4(uint32_t addr, uint32_t r0, uint32_t r1, uint32_t r2, uint32_t r3) {
    asm volatile("stmatrix.sync.aligned.m8n8.x4.shared.b16 [%0], {%1,%2,%3,%4};" :: "r"(addr), "r"(r0), "r"(r1), "r"(r2), "r"(r3) : "memory");
}
__device__ __forceinline__ void bulk_store(void* dst, uint32_t src, uint32_t bytes) {
    asm volatile("cp.async.bulk.global.shared::cta.bulk_group [%0], [%1], %2;" :: "l"(dst), "r"(src), "r"(bytes) : "memory");
}
#define FENCE_ASYNC() asm volatile("fence.proxy.async.shared::cta;" ::: "memory")

__device__ __forceinline__ void k1_stage_rows(const uint32_t (&pk)[40], uint32_t base, bool odd) {
    const uint32_t b0 = base + (odd ? 512 : 0), b2 = base + (odd ? 0 : 2048);
    #pragma unroll
    for (int j = 0; j < 16; j += 2) stsm4(b0 + j * 128, pk[2*j], pk[2*j+1], pk[2*j+2], pk[2*j+3]);
    #pragma unroll
    for (int j = 0; j < 4; j += 2) stsm4(b2 + j * 128, pk[32 + 2*j], pk[33 + 2*j], pk[34 + 2*j], pk[35 + 2*j]);
}
template<bool ODD>
__device__ __forceinline__ void k1_image(const uint32_t (&pk)[40], uint32_t base, int lane) {
    #define PH(j) (ODD ? ((j) < 4 ? (j) + 16 : (j) - 4) : (j))
    const bool hi = lane & 16;
    #pragma unroll
    for (int i = 0; i < 4; i++) {
        const uint32_t e = base + (2 * i) * 12288, o = e + 12288;
        const int j = 5 * i;
        stsm4(hi ? e + 128 : e, pk[2*PH(j)], pk[2*PH(j)+1], pk[2*PH(j+1)], pk[2*PH(j+1)+1]);
        stsm4(hi ? o : e + 256, pk[2*PH(j+2)], pk[2*PH(j+2)+1], pk[2*PH(j+2)], pk[2*PH(j+2)+1]);
        stsm4(hi ? o + 256 : o + 128, pk[2*PH(j+3)], pk[2*PH(j+3)+1], pk[2*PH(j+4)], pk[2*PH(j+4)+1]);
    }
}
template<bool ODD>
__device__ __forceinline__ void k1_norms(const uint32_t (&pk)[40], int lane, float* kn_dst) {
    {
        const bool lo = (lane & 3) < 2;
        #pragma unroll
        for (int h = 0; h < 8; h++) {
            float a = 0.f, b = 0.f;
            #pragma unroll
            for (int jj = 0; jj < 3; jj++) {
                const int j = (5 * h) / 2 + jj;
                const uint32_t v0 = pk[2*PH(j)], v1 = pk[2*PH(j)+1];
                float s0 = bflo(v0) * bflo(v0) + bfhi(v0) * bfhi(v0), s1 = bflo(v1) * bflo(v1) + bfhi(v1) * bfhi(v1);
                if (jj == ((h & 1) ? 0 : 2)) { const bool mine = (h & 1) ? !lo : lo; s0 = mine ? s0 : 0.f; s1 = mine ? s1 : 0.f; }
                a += s0; b += s1;
            }
            a += __shfl_xor_sync(0xffffffffu, a, 1); b += __shfl_xor_sync(0xffffffffu, b, 1);
            a += __shfl_xor_sync(0xffffffffu, a, 2); b += __shfl_xor_sync(0xffffffffu, b, 2);
            a = fmaxf(a, b);
            a = fmaxf(a, __shfl_xor_sync(0xffffffffu, a, 4));
            a = fmaxf(a, __shfl_xor_sync(0xffffffffu, a, 8));
            a = fmaxf(a, __shfl_xor_sync(0xffffffffu, a, 16));
            if (lane == h) kn_dst[h * 128] = a;
        }
    }
    #undef PH
}

struct WMaps { CUtensorMap m[4]; };
__global__ void __launch_bounds__(512, 1)
qkv_kernel(const __grid_constant__ CUtensorMap tm_x, const __grid_constant__ WMaps tm_w,
           const __nv_bfloat16* __restrict__ x, const __nv_bfloat16* __restrict__ gate_w,
           const __nv_bfloat16* __restrict__ woa, const __nv_bfloat16* __restrict__ wob) {
    extern __shared__ __align__(1024) uint8_t smem[];
    const uint32_t sb = smem_u32(smem);
    const int tid = threadIdx.x, warp = tid >> 5, lane = tid & 31;
    const int mt = ((blockIdx.x >> 4) & 3) * 4 + (blockIdx.x & 3), grp = (blockIdx.x >> 6) * 4 + ((blockIdx.x >> 2) & 3), br = grp >> 2, hg = grp & 3;
    const CUtensorMap* tw = &tm_w.m[br * 2];
    TS_MIN(0); CK(0, 0);
    if (tid == 0) {
        for (int i = 0; i < 5; i++) { mbar_init(K1_BAR(i), 1); mbar_init(K1_BAR(5 + i), 16); }
        for (int i = 0; i < 3; i++) { mbar_init(K1_BAR(10 + i), 1); mbar_init(K1_BAR(13 + i), 16); }
        mbar_init(K1_BAR(16), 16); mbar_init(K1_BAR(17), 16); mbar_init(K1_BAR(18), 12);
        asm volatile("fence.mbarrier_init.release.cluster;" ::: "memory");
        k1_issue(1, 0, sb, &tm_x, tw, mt, hg);
    }
    __syncthreads();
    GRIDDEP_LAUNCH();
    if (tid == 0) for (int i = 1; i < 5; i++) k1_issue(1, i, sb, &tm_x, tw, mt, hg);
    if (tid == 32) {
        l2_prefetch(woa + blockIdx.x * 5 * DM, 6400);
        l2_prefetch(wob + blockIdx.x * 5 * DM, 6400);
    }
    if (tid >= 64 && tid < 96) *(uint32_t*)(smem + K1_ONES + lane * 4) = (lane & 3) == 0 ? 0x3F80u : 0u;
    __syncwarp();
    const int wg = __shfl_sync(0xffffffffu, warp >> 2, 0), mh = wg & 1, sel = wg >> 1, w4 = warp & 3;
    const int g = lane >> 2, t = lane & 3;
    const bool odd = hg & 1;
    CK(0, 1);
    {
        float a0[32], a2[16];
        #pragma unroll
        for (int i = 0; i < 32; i++) a0[i] = 0.f;
        #pragma unroll
        for (int i = 0; i < 16; i++) a2[i] = 0.f;
        fence_f(a0); fence_f(a2);
        const uint32_t o0 = sel ? 512 : (odd ? 1024 : 0), o2 = odd ? 4 : 1024;
        for (int kb = 0; kb < 10; kb++) {
            const int s = kb % 5;
            mbar_wait(K1_BAR(s), kb >= 5);
            const uint32_t st = sb + s * 40960;
            const uint64_t da = mkdesc(st + mh * 8192, 16, 1024, 1), db = mkdesc(st + 16384, 8192, 1024, 1);
            WG_FENCE();
            #pragma unroll
            for (int k = 0; k < 4; k++) wg_ss_n64_bt(a0, da + k * 2, db + o0 + k * 128, 1);
            if (sel) {
                #pragma unroll
                for (int k = 0; k < 4; k++) wg_ss_n32_bt(a2, da + k * 2, db + o2 + k * 128, 1);
            }
            WG_COMMIT();
            WG_WAIT(0);
            if (lane == 0) mbar_arrive(K1_BAR(5 + s));
            if (tid == 0) {
                mbar_wait(K1_BAR(5 + s), kb >= 5);
                if (kb < 5) k1_issue(1, kb + 5, sb, &tm_x, tw, mt, hg);
                else if (kb == 6) k1_issue(0, 0, sb, &tm_x, tw, mt, hg);
                else if (kb >= 8) k1_issue(0, kb - 7, sb, &tm_x, tw, mt, hg);
            }
            __syncwarp();
        }
        fence_f(a0); fence_f(a2);
        CK(0, 2);
        uint8_t* dst = (br ? g_qb : g_pq) + ((mt * 16 + mh * 8 + w4 * 2) * 80 + hg * 20) * 128 + lane * 4;
        uint8_t* d0 = dst + (sel ? (odd ? 4 : 8) : (odd ? 12 : 0)) * 128;
        uint8_t* d2 = dst + (odd ? 0 : 16) * 128;
        if (br) {
            #pragma unroll
            for (int j = 0; j < 8; j++) {
                *(uint32_t*)(d0 + j * 128) = packbf(a0[4*j] * QSCALE, a0[4*j+1] * QSCALE);
                *(uint32_t*)(d0 + 10240 + j * 128) = packbf(a0[4*j+2] * QSCALE, a0[4*j+3] * QSCALE);
            }
            if (sel) {
                #pragma unroll
                for (int j = 0; j < 4; j++) {
                    *(uint32_t*)(d2 + j * 128) = packbf(a2[4*j] * QSCALE, a2[4*j+1] * QSCALE);
                    *(uint32_t*)(d2 + 10240 + j * 128) = packbf(a2[4*j+2] * QSCALE, a2[4*j+3] * QSCALE);
                }
            }
        } else {
            #pragma unroll
            for (int j = 0; j < 8; j++) {
                *(uint32_t*)(d0 + j * 128) = packbf(phi_f(a0[4*j]), phi_f(a0[4*j+1]));
                *(uint32_t*)(d0 + 10240 + j * 128) = packbf(phi_f(a0[4*j+2]), phi_f(a0[4*j+3]));
            }
            if (sel) {
                #pragma unroll
                for (int j = 0; j < 4; j++) {
                    *(uint32_t*)(d2 + j * 128) = packbf(phi_f(a2[4*j]), phi_f(a2[4*j+1]));
                    *(uint32_t*)(d2 + 10240 + j * 128) = packbf(phi_f(a2[4*j+2]), phi_f(a2[4*j+3]));
                }
            }
        }
    }
    CK(0, 3);
    uint32_t pk[40];
    {
        float a0[64], a2[16];
        #pragma unroll
        for (int i = 0; i < 64; i++) a0[i] = 0.f;
        #pragma unroll
        for (int i = 0; i < 16; i++) a2[i] = 0.f;
        fence_f(a0); fence_f(a2);
        const uint32_t o0 = odd ? 512 : 0, o2 = odd ? 4 : 1024;
        const uint32_t arow = (mh * 64 + w4 * 16 + (lane & 15)) * 128;
        for (int kb = 0; kb < 10; kb++) {
            const int s = kb % 3;
            mbar_wait(K1_BAR(10 + s), (kb / 3) & 1);
            const uint32_t st = sb + s * 65536;
            const uint64_t db = mkdesc(st + 16384 + sel * 24576, 8192, 1024, 1);
            uint32_t af[4][4];
            #pragma unroll
            for (int k = 0; k < 4; k++)
                asm volatile("ldmatrix.sync.aligned.m8n8.x4.shared.b16 {%0,%1,%2,%3}, [%4];"
                    : "=r"(af[k][0]), "=r"(af[k][1]), "=r"(af[k][2]), "=r"(af[k][3]) : "r"(st + arow + (((2 * k + (lane >> 4)) ^ (lane & 7)) << 4)));
            WG_FENCE();
            #pragma unroll
            for (int k = 0; k < 4; k++) {
                wg_rs_n128_bt(a0, af[k][0], af[k][1], af[k][2], af[k][3], db + o0 + k * 128);
                wg_rs_n32_bt(a2, af[k][0], af[k][1], af[k][2], af[k][3], db + o2 + k * 128);
            }
            WG_COMMIT();
            WG_WAIT(0);
            const uint32_t eb = K1_BAR(kb == 9 ? 16 : 13 + s);
            if (lane == 0) mbar_arrive(eb);
            if (tid == 0 && kb < 7) { mbar_wait(eb, (kb / 3) & 1); k1_issue(0, kb + 3, sb, &tm_x, tw, mt, hg); }
            __syncwarp();
        }
        fence_f(a0); fence_f(a2);
        CK(0, 4);
        if (br == 0 && sel == 0) {
            #pragma unroll
            for (int i = 0; i < 32; i++) pk[i] = packbf(phi_f(a0[2 * i]), phi_f(a0[2 * i + 1]));
            #pragma unroll
            for (int i = 0; i < 8; i++) pk[32 + i] = packbf(phi_f(a2[2 * i]), phi_f(a2[2 * i + 1]));
        } else {
            #pragma unroll
            for (int i = 0; i < 32; i++) pk[i] = packbf(a0[2 * i], a0[2 * i + 1]);
            #pragma unroll
            for (int i = 0; i < 8; i++) pk[32 + i] = packbf(a2[2 * i], a2[2 * i + 1]);
        }
    }
    const int rg = mh * 8 + w4 * 2 + ((lane >> 3) & 1);
    mbar_wait(K1_BAR(14), 0); mbar_wait(K1_BAR(15), 0);
    const uint32_t stg = sb + 65536;
    bool do_gate;
    if (br) {
        const uint32_t base = stg + rg * 768 + sel * 384 + (lane & 7) * 16;
        if (odd) k1_image<true>(pk, base, lane); else k1_image<false>(pk, base, lane);
        __syncwarp();
        {
            const int lr = mh * 64 + w4 * 16 + (lane & 15);
            const uint32_t flag = (sel == 0 && ((POLY_MASK >> ((lr >> 3) & 15)) & 1)) ? 0x3F80u : 0u;
            const uint2 cv = make_uint2(0x3F80u | (flag << 16), flag);
            uint8_t* p = smem + 65536 + (lane >> 4) * 49152 + (lr >> 3) * 768 + sel * 384 + (lr & 7) * 16;
            *(uint2*)(p + 264) = cv; *(uint2*)(p + 12288) = cv; *(uint2*)(p + 24576 + 264) = cv; *(uint2*)(p + 36864) = cv;
        }
        FENCE_ASYNC();
        __syncwarp();
        if (lane == 0) mbar_arrive(K1_BAR(17));
        if (warp == 8 && lane < 8) {
            mbar_wait(K1_BAR(17), 0);
            bulk_store(g_kvimg + (size_t)(hg * 8 + lane) * 196608 + mt * 12288, stg + lane * 12288, 12288);
            asm volatile("cp.async.bulk.commit_group;" ::: "memory");
        }
        __syncwarp();
        if (sel == 0) {
            float* kd = g_kn2 + (hg * 8) * 128 + mt * 8 + mh * 4 + w4;
            if (odd) k1_norms<true>(pk, lane, kd); else k1_norms<false>(pk, lane, kd);
        }
        do_gate = sel == 1;
    } else {
        k1_stage_rows(pk, stg + rg * 5120 + sel * 2560 + (lane >> 4) * 128 + (lane & 7) * 16, odd);
        FENCE_ASYNC();
        __syncwarp();
        if (lane == 0) mbar_arrive(K1_BAR(17));
        if (wg != 0) {
            const int mi = wg - 1;
            mbar_wait(K1_BAR(17), 0);
            float* kvo = (float*)(smem + 65536 + 81920);
            float kv[44], zz[4];
            #pragma unroll
            for (int i = 0; i < 44; i++) kv[i] = 0.f;
            zz[0] = zz[1] = zz[2] = zz[3] = 0.f;
            fence_f(kv); fence_f(zz);
            const int vs = mi == 0 ? 0 : (mi == 1 ? 56 : 72);
            const uint64_t da = mkdesc(stg + mi * 1024, 5120, 128, 0);
            const uint64_t db = mkdesc(stg + 2560 + (vs >> 3) * 128, 5120, 128, 0);
            const uint64_t d1 = mkdesc(sb + K1_ONES, 0, 128, 0);
            WG_FENCE();
            #pragma unroll
            for (int k = 0; k < 8; k++) {
                wg_ss_n88_atbt(kv, da + k * 640, db + k * 640, 1);
                wg_ss_n8_atbt(zz, da + k * 640, d1, 1);
            }
            WG_COMMIT();
            WG_WAIT(0);
            fence_f(kv); fence_f(zz);
            #pragma unroll
            for (int r = 0; r < 2; r++) {
                const int pc = mi * 64 + w4 * 16 + g + 8 * r;
                if (pc < 160) {
                    const int e0 = vs + 2 * t - (pc / 20) * 20;
                    #pragma unroll
                    for (int j = 0; j < 11; j++) {
                        const int e = e0 + 8 * j;
                        if (e >= 0 && e < 20) *(float2*)(kvo + pc * 24 + e) = make_float2(kv[4*j + 2*r], kv[4*j + 2*r + 1]);
                    }
                    if (t == 0) kvo[3840 + pc] = zz[2 * r];
                }
            }
            FENCE_ASYNC();
            __syncwarp();
            if (lane == 0) mbar_arrive(K1_BAR(18));
            if (tid == 256) {
                mbar_wait(K1_BAR(18), 0);
                bulk_store(g_kvpart + (size_t)(mt * NH + hg * 8) * 480, stg + 81920, 15360);
                bulk_store(g_zpart + (mt * NH + hg * 8) * 20, stg + 97280, 640);
                asm volatile("cp.async.bulk.commit_group;" ::: "memory");
            }
            __syncwarp();
        }
        do_gate = wg == 0;
    }
    if (do_gate) {
        const int nr = br ? 2 : 4;
        #pragma unroll 1
        for (int r0 = 0; r0 < nr; r0 += 2) {
            const int row = mt * 128 + grp * 16 + (warp & 7) * nr + r0;
            float s0 = 0.f, s1 = 0.f;
            uint4 v0[3], v1[3], w[3];
            #pragma unroll
            for (int c = 0; c < 3; c++) {
                const int ch = min(lane + 32 * c, 79);
                v0[c] = *(const uint4*)(x + row * DM + ch * 8); v1[c] = *(const uint4*)(x + (row + 1) * DM + ch * 8); w[c] = *(const uint4*)(gate_w + ch * 8);
            }
            if (lane >= 16) w[2] = make_uint4(0, 0, 0, 0);
            #pragma unroll
            for (int c = 0; c < 3; c++) {
                s0 += bflo(v0[c].x) * bflo(w[c].x) + bfhi(v0[c].x) * bfhi(w[c].x) + bflo(v0[c].y) * bflo(w[c].y) + bfhi(v0[c].y) * bfhi(w[c].y)
                    + bflo(v0[c].z) * bflo(w[c].z) + bfhi(v0[c].z) * bfhi(w[c].z) + bflo(v0[c].w) * bflo(w[c].w) + bfhi(v0[c].w) * bfhi(w[c].w);
                s1 += bflo(v1[c].x) * bflo(w[c].x) + bfhi(v1[c].x) * bfhi(w[c].x) + bflo(v1[c].y) * bflo(w[c].y) + bfhi(v1[c].y) * bfhi(w[c].y)
                    + bflo(v1[c].z) * bflo(w[c].z) + bfhi(v1[c].z) * bfhi(w[c].z) + bflo(v1[c].w) * bflo(w[c].w) + bfhi(v1[c].w) * bfhi(w[c].w);
            }
            #pragma unroll
            for (int o = 16; o; o >>= 1) { s0 += __shfl_xor_sync(0xffffffffu, s0, o); s1 += __shfl_xor_sync(0xffffffffu, s1, o); }
            if (lane < 2) g_gate[row + lane] = 1.f / (1.f + __expf(-(lane ? s1 : s0)));
        }
    }
    if (warp == 8) asm volatile("cp.async.bulk.wait_group.read 0;" ::: "memory");
    TS_MAX(3); CK(0, 5);
}

#define K2_SMEM (196608 + 12288 + 1024)
#define PQN_LATE 0
#define LOOPV 0
struct PolyC { uint32_t one, cm15, c3, c2, c1, c0; };
__device__ __forceinline__ uint32_t hfma2bf(uint32_t a, uint32_t b, uint32_t c) { uint32_t r; asm("fma.rn.bf16x2 %0, %1, %2, %3;" : "=r"(r) : "r"(a), "r"(b), "r"(c)); return r; }
__device__ __forceinline__ uint32_t hadd2bf(uint32_t a, uint32_t b) { uint32_t r; asm("add.rn.bf16x2 %0, %1, %2;" : "=r"(r) : "r"(a), "r"(b)); return r; }
__device__ __forceinline__ uint32_t exp2_poly2(float y0, float y1, const PolyC& pc) {
    const uint32_t sch = __byte_perm(__float_as_uint(y0), __float_as_uint(y1), 0x6521);
    uint32_t m; asm("lop3.b32 %0, %1, 0x007F007F, %2, 0xEA;" : "=r"(m) : "r"(sch), "r"(pc.one));
    return hfma2bf(hfma2bf(m, pc.c2, pc.c1), m, pc.c0) + sch;
    const uint32_t d = hadd2bf(m, pc.cm15);
    uint32_t r = hfma2bf(d, pc.c2, pc.c1);
    r = hfma2bf(r, d, pc.c0);
    return r + sch;
}
template<int PAR>
__device__ __forceinline__ void softmax_blk(const float (&s)[32], uint32_t (&p)[16], const PolyC& pc) {
    #pragma unroll
    for (int j = 0; j < 8; j++) {
        if ((POLY_MASK >> (PAR * 8 + j)) & 1) {
            p[2*j] = exp2_poly2(s[4*j], s[4*j+1], pc);
            p[2*j+1] = exp2_poly2(s[4*j+2], s[4*j+3], pc);
        } else {
            p[2*j] = packbf(ex2f(s[4*j]), ex2f(s[4*j+1]));
            p[2*j+1] = packbf(ex2f(s[4*j+2]), ex2f(s[4*j+3]));
        }
    }
}

template<int HALF>
__device__ __forceinline__ void softmax_half(const float (&s)[64], uint32_t (&p)[16], const PolyC& pc) {
    #pragma unroll
    for (int j = 0; j < 8; j++) {
        const int b = 32 * HALF + 4 * j;
        if ((POLY_MASK >> (HALF * 8 + j)) & 1) {
            p[2*j] = exp2_poly2(s[b], s[b+1], pc);
            p[2*j+1] = exp2_poly2(s[b+2], s[b+3], pc);
        } else {
            p[2*j] = packbf(ex2f(s[b]), ex2f(s[b+1]));
            p[2*j+1] = packbf(ex2f(s[b+2]), ex2f(s[b+3]));
        }
    }
}

__device__ __noinline__ void aux_work(uint8_t* smem, int ax, const __nv_bfloat16* __restrict__ a_wo) {
    float* kvs = (float*)smem;
    const int tid = threadIdx.x;
    for (int i = tid; i < 3840; i += 512) {
        float s = 0.f;
        #pragma unroll
        for (int m = 0; m < 16; m++) s += g_kvpart[(size_t)(m * NH + ax * 8) * 480 + i];
        kvs[i] = s;
    }
    __syncthreads();
    #pragma unroll 1
    for (int it = tid; it < 8 * 5 * 80; it += 512) {
        const int cc = it % 80, dq = (it / 80) % 5, h = it / 400;
        float a[4][8];
        #pragma unroll
        for (int r = 0; r < 4; r++)
            #pragma unroll
            for (int i = 0; i < 8; i++) a[r][i] = 0.f;
        const __nv_bfloat16* wp = a_wo + (size_t)((ax * 8 + h) * DH) * DM + cc * 8;
        const float* kp = kvs + (h * 20 + dq * 4) * 24;
        #pragma unroll 5
        for (int e = 0; e < 20; e++) {
            const uint4 w = *(const uint4*)(wp + e * DM);
            const float wf[8] = {bflo(w.x), bfhi(w.x), bflo(w.y), bfhi(w.y), bflo(w.z), bfhi(w.z), bflo(w.w), bfhi(w.w)};
            #pragma unroll
            for (int r = 0; r < 4; r++) {
                const float k = kp[r * 24 + e];
                #pragma unroll
                for (int i = 0; i < 8; i++) a[r][i] += k * wf[i];
            }
        }
        #pragma unroll
        for (int r = 0; r < 4; r++)
            *(uint4*)(g_wm + (size_t)((ax * 8 + h) * DH + dq * 4 + r) * DM + cc * 8) =
                make_uint4(packbf(a[r][0], a[r][1]), packbf(a[r][2], a[r][3]), packbf(a[r][4], a[r][5]), packbf(a[r][6], a[r][7]));
    }
}

__global__ void __launch_bounds__(512, 1)
attn_kernel(const __nv_bfloat16* __restrict__ a_wo) {
    extern __shared__ __align__(1024) uint8_t smem[];
    const uint32_t sb = smem_u32(smem);
    const uint32_t bars = sb + 196608 + 12288;
    const int tid = threadIdx.x, warp = tid >> 5, lane = tid & 31;
    GRIDDEP_LAUNCH();
    if (blockIdx.x < 4) {
        GRIDDEP_WAIT();
        aux_work(smem, blockIdx.x, a_wo);
        TS_MAX(13);
        return;
    }
    const int h = (blockIdx.x - 4) >> 2, qb = blockIdx.x & 3;
    if (tid == 0) {
        for (int i = 0; i < 17; i++) mbar_init(bars + 8 * i, 1);
        asm volatile("fence.mbarrier_init.release.cluster;" ::: "memory");
        mbar_arrive(bars + 128);
    }
    TS_MIN(4);
    GRIDDEP_WAIT();
    TS_MIN(5); TS_MAX(17); CK(1, 0);
    const int wg = warp >> 2, w4 = warp & 3, g = lane >> 2, t = lane & 3;
    const uint8_t* kvsrc = g_kvimg + (size_t)h * 196608;
    if (tid == 0) {
        for (int i = 0; i < 2; i++) { mbar_expect(bars + 8 * i, 12288); bulk_load(sb + i * 12288, kvsrc + i * 12288, 12288, bars + 8 * i); }
    }
    const int rbase = qb * 512 + wg * 128 + w4 * 16 + g;
    const int fb = (5 * h) >> 1;
    const bool odd = h & 1;
    const bool cslot = odd ? t < 2 : t >= 2;
    uint32_t qv[4][3], pv[4][3];
    float gt[4], kmax, zs = 0.f;
    {
        const uint32_t qo = ((rbase >> 3) * 80 + fb) * 128 + lane * 4;
        #pragma unroll
        for (int r = 0; r < 4; r++) {
            const uint32_t ro = qo + ((r & 1) + (r >> 1) * 8) * 10240;
            qv[r][0] = *(const uint32_t*)(g_qb + ro); qv[r][1] = *(const uint32_t*)(g_qb + ro + 128); qv[r][2] = *(const uint32_t*)(g_qb + ro + 256);
            pv[r][0] = *(const uint32_t*)(g_pq + ro); pv[r][1] = *(const uint32_t*)(g_pq + ro + 128); pv[r][2] = *(const uint32_t*)(g_pq + ro + 256);
            gt[r] = g_gate[rbase + (r & 1) * 8 + (r >> 1) * 64];
        }
        {
            const int d = lane - (odd ? 4 : 0);
            if (d >= 0 && d < 20) {
                #pragma unroll
                for (int m = 0; m < 16; m++) zs += g_zpart[(m * NH + h) * 20 + d];
            }
        }
        const float4 kn4 = *(const float4*)(g_kn2 + h * 128 + lane * 4);
        float kn = fmaxf(fmaxf(kn4.x, kn4.y), fmaxf(kn4.z, kn4.w));
        #pragma unroll
        for (int o = 16; o; o >>= 1) kn = fmaxf(kn, __shfl_xor_sync(0xffffffffu, kn, o));
        kmax = sqrtf(kn);
        if (cslot) {
            #pragma unroll
            for (int r = 0; r < 4; r++) { if (odd) qv[r][0] = 0u; else qv[r][2] = 0u; }
        }
        CK(1, 3);
        __syncthreads();
        CK(1, 4);
        if (tid == 0) {
            for (int i = 2; i < 16; i++) { mbar_expect(bars + 8 * i, 12288); bulk_load(sb + i * 12288, kvsrc + i * 12288, 12288, bars + 8 * i); }
        }
        __syncwarp();
        float z[6];
        #pragma unroll
        for (int j = 0; j < 3; j++) { z[2*j] = __shfl_sync(0xffffffffu, zs, 8 * j + 2 * t); z[2*j+1] = __shfl_sync(0xffffffffu, zs, 8 * j + 2 * t + 1); }
        #pragma unroll
        for (int r = 0; r < 4; r++) {
            float den = bflo(pv[r][0]) * z[0] + bfhi(pv[r][0]) * z[1] + bflo(pv[r][1]) * z[2] + bfhi(pv[r][1]) * z[3] + bflo(pv[r][2]) * z[4] + bfhi(pv[r][2]) * z[5];
            den += __shfl_xor_sync(0xffffffffu, den, 1);
            den += __shfl_xor_sync(0xffffffffu, den, 2);
            const float sc = gt[r] / (den + 1e-6f);
            const int tg = (rbase >> 3) + (r & 1) + (r >> 1) * 8;
            #pragma unroll
            for (int j = 0; j < 3; j++) {
                const int kb = fb + j;
                if (!(cslot && j == (odd ? 0 : 2)))
                    *(uint32_t*)(g_acat + (((kb >> 3) * 256 + tg) * 8 + (kb & 7)) * 128 + lane * 4) = packbf(bflo(pv[r][j]) * sc, bfhi(pv[r][j]) * sc);
            }
        }
    }
    PolyC pc;
    asm volatile("mov.b32 %0, 0x3F803F80;" : "=r"(pc.one));
    asm volatile("mov.b32 %0, 0xBFC0BFC0;" : "=r"(pc.cm15));
    pc.c3 = 0;
    asm volatile("mov.b32 %0, 0x42304230;" : "=r"(pc.c2));
    asm volatile("mov.b32 %0, 0xBF7CBF7C;" : "=r"(pc.c1));
    asm volatile("mov.b32 %0, 0x43744375;" : "=r"(pc.c0));
    pc.c2 = 0x42274229u + blockIdx.y;
    pc.one = 0x3F803F80u + blockIdx.y;
    asm volatile("mov.b32 %0, 0xC2FDC300;" : "=r"(pc.c1));
    asm volatile("mov.b32 %0, 0x43AA43AB;" : "=r"(pc.c0));

    #pragma unroll 1
    for (int tile = 0; tile < 2; tile++) {
        const int row0 = rbase + tile * 64;
        uint32_t q[8];
        q[0] = tile ? qv[2][0] : qv[0][0]; q[1] = tile ? qv[3][0] : qv[1][0];
        q[2] = tile ? qv[2][1] : qv[0][1]; q[3] = tile ? qv[3][1] : qv[1][1];
        q[4] = tile ? qv[2][2] : qv[0][2]; q[5] = tile ? qv[3][2] : qv[1][2];
        q[6] = blockIdx.y; q[7] = blockIdx.y;
        const float gt0 = tile ? gt[2] : gt[0], gt1 = tile ? gt[3] : gt[1];
        float n0 = bflo(q[0]) * bflo(q[0]) + bfhi(q[0]) * bfhi(q[0]) + bflo(q[2]) * bflo(q[2]) + bfhi(q[2]) * bfhi(q[2]) + bflo(q[4]) * bflo(q[4]) + bfhi(q[4]) * bfhi(q[4]);
        float n1 = bflo(q[1]) * bflo(q[1]) + bfhi(q[1]) * bfhi(q[1]) + bflo(q[3]) * bflo(q[3]) + bfhi(q[3]) * bfhi(q[3]) + bflo(q[5]) * bflo(q[5]) + bfhi(q[5]) * bfhi(q[5]);
        n0 += __shfl_xor_sync(0xffffffffu, n0, 1); n1 += __shfl_xor_sync(0xffffffffu, n1, 1);
        n0 += __shfl_xor_sync(0xffffffffu, n0, 2); n1 += __shfl_xor_sync(0xffffffffu, n1, 2);
        const float m0 = sqrtf(n0) * kmax * 1.02f + 0.0625f, m1 = sqrtf(n1) * kmax * 1.02f + 0.0625f;
        uint32_t unsafe = !(m0 <= 48.f && m1 <= 48.f);
        asm volatile("{.reg .pred p, q; setp.ne.u32 p, %0, 0; barrier.red.or.pred q, %1, 128, p; selp.u32 %0, 1, 0, q;}" : "+r"(unsafe) : "r"(wg + 1) : "memory");
        unsafe = __any_sync(0xffffffffu, unsafe);

        CK(1, 8 + tile * 3);
        float o[12];
        #pragma unroll
        for (int i = 0; i < 12; i++) o[i] = 0.f;
        fence_f(o);
        const uint64_t dk = mkdesc(sb, 128, 768, 0), dk2 = mkdesc(sb + 256, 0, 768, 0), dv = mkdesc(sb + 384, 768, 128, 0);
        float S[32];
        uint32_t p[16];
        if (!unsafe) {
            if (cslot) {
                const uint32_t c0 = (t & 1) ? 0x3B80u : ((packbf(-m0, 0.f) & 0xFFFFu) | 0x43FC0000u);
                const uint32_t c1 = (t & 1) ? 0x3B80u : ((packbf(-m1, 0.f) & 0xFFFFu) | 0x43FC0000u);
                if (odd) { q[0] = c0; q[1] = c1; } else { q[4] = c0; q[5] = c1; }
            }
            uint64_t ck = dk, ck2 = dk2, cv = dv;
            uint32_t cb = bars;
            mbar_wait(cb, 0);
            WG_FENCE();
            wg_qk0(S, q[0], q[1], q[2], q[3], ck); wg_qk1(S, q[4], q[5], q[6], q[7], ck2);
            WG_COMMIT();
            WG_WAIT(0);
            fence_f(S);
            #pragma unroll 1
            for (int c = 0; c < 16; c++) {
                softmax_blk<0>(S, p, pc);
                fence_r(p);
                WG_FENCE();
                wg_qk0(S, q[0], q[1], q[2], q[3], ck + 384); wg_qk1(S, q[4], q[5], q[6], q[7], ck2 + 384);
                #pragma unroll
                for (int k = 0; k < 4; k++) wg_pv(o, p[4*k], p[4*k+1], p[4*k+2], p[4*k+3], cv + k * 96);
                WG_COMMIT();
                WG_WAIT(0);
                fence_f(S);
                softmax_blk<1>(S, p, pc);
                fence_r(p);
                cb += 8; ck += 768; ck2 += 768;
                mbar_wait(cb, 0);
                WG_FENCE();
                wg_qk0(S, q[0], q[1], q[2], q[3], ck); wg_qk1(S, q[4], q[5], q[6], q[7], ck2);
                #pragma unroll
                for (int k = 0; k < 4; k++) wg_pv(o, p[4*k], p[4*k+1], p[4*k+2], p[4*k+3], cv + 384 + k * 96);
                WG_COMMIT();
                cv += 768;
                WG_WAIT(0);
                fence_f(S);
            }
        } else {
            float rm0 = -INFINITY, rm1 = -INFINITY;
            #pragma unroll 1
            for (int b = 0; b < 32; b++) {
                if ((b & 1) == 0) mbar_wait(bars + 8 * (b >> 1), 0);
                WG_FENCE();
                wg_qk0(S, q[0], q[1], q[2], q[3], dk + b * 384); wg_qk1(S, q[4], q[5], q[6], q[7], dk2 + b * 384);
                WG_COMMIT();
                WG_WAIT(0);
                fence_f(S);
                float x0 = rm0, x1 = rm1;
                #pragma unroll
                for (int j = 0; j < 8; j++) { x0 = fmaxf(x0, fmaxf(S[4*j], S[4*j+1])); x1 = fmaxf(x1, fmaxf(S[4*j+2], S[4*j+3])); }
                x0 = fmaxf(x0, __shfl_xor_sync(0xffffffffu, x0, 1)); x1 = fmaxf(x1, __shfl_xor_sync(0xffffffffu, x1, 1));
                x0 = fmaxf(x0, __shfl_xor_sync(0xffffffffu, x0, 2)); x1 = fmaxf(x1, __shfl_xor_sync(0xffffffffu, x1, 2));
                const float c0 = ex2f(rm0 - x0), c1 = ex2f(rm1 - x1);
                rm0 = x0; rm1 = x1;
                #pragma unroll
                for (int j = 0; j < 3; j++) { o[4*j] *= c0; o[4*j+1] *= c0; o[4*j+2] *= c1; o[4*j+3] *= c1; }
                #pragma unroll
                for (int j = 0; j < 8; j++) {
                    p[2*j] = packbf(ex2f(S[4*j] - x0), ex2f(S[4*j+1] - x0));
                    p[2*j+1] = packbf(ex2f(S[4*j+2] - x1), ex2f(S[4*j+3] - x1));
                }
                fence_r(p); fence_f(o);
                WG_FENCE();
                #pragma unroll
                for (int k = 0; k < 4; k++) wg_pv(o, p[4*k], p[4*k+1], p[4*k+2], p[4*k+3], dv + b * 384 + k * 96);
                WG_COMMIT();
                WG_WAIT(0);
                fence_f(o);
            }
        }
        fence_f(o);
        CK(1, 9 + tile * 3);
        const int src = (lane & ~3) | (odd ? 0 : 2);
        const float l0 = __shfl_sync(0xffffffffu, odd ? o[0] : o[8], src), l1 = __shfl_sync(0xffffffffu, odd ? o[2] : o[10], src);
        const float s0 = (1.f - gt0) / l0, s1 = (1.f - gt1) / l1;
        #pragma unroll
        for (int j = 0; j < 3; j++) {
            const int kb = 80 + fb + j;
            uint8_t* dst = g_acat + (((kb >> 3) * 256 + (row0 >> 3)) * 8 + (kb & 7)) * 128 + lane * 4;
            if (!(cslot && j == (odd ? 0 : 2))) {
                *(uint32_t*)dst = packbf(o[4*j] * s0, o[4*j+1] * s0);
                *(uint32_t*)(dst + 1024) = packbf(o[4*j+2] * s1, o[4*j+3] * s1);
            }
        }
    }
    TS_MAX(7);
}

__constant__ uint8_t k3_map[130] = {0,1,2,3,16,17,18,19,32,33,34,35,48,49,50,51,4,5,6,7,20,21,22,23,36,37,38,39,52,53,54,55,8,9,24,25,40,41,56,57,64,65,66,67,80,81,82,83,96,97,98,99,112,113,114,115,68,69,70,71,84,85,86,87,100,101,102,103,116,117,118,119,72,73,88,89,104,105,120,121,128,129,130,131,144,145,146,147,160,161,162,163,176,177,178,179,132,133,134,135,148,149,150,151,164,165,166,167,180,181,182,183,136,137,152,153,168,169,184,185,192,193,194,195,196,197,198,199,200,201};
#define K3_STAGE 28672
#define K3_NST 7
#define K3_SMEM (K3_NST * K3_STAGE + 1024)
__global__ void __launch_bounds__(160, 1)
out_kernel(const __grid_constant__ CUtensorMap tm_wm, const __grid_constant__ CUtensorMap tm_wob,
           __nv_bfloat16* __restrict__ out) {
    extern __shared__ __align__(1024) uint8_t smem[];
    const uint32_t sb = smem_u32(smem);
    const uint32_t bar_full = sb + K3_NST * K3_STAGE, bar_empty = bar_full + 64;
    const int tid = threadIdx.x, warp = tid >> 5, lane = tid & 31;
    const int tt = k3_map[blockIdx.x] >> 4, ct = k3_map[blockIdx.x] & 15;
    if (tid == 0) {
        for (int i = 0; i < K3_NST; i++) { mbar_init(bar_full + 8 * i, 1); mbar_init(bar_empty + 8 * i, 4); }
        asm volatile("fence.mbarrier_init.release.cluster;" ::: "memory");
    }
    __syncthreads();
    CK3(0);
    if (warp == 4) {
        if (lane == 0) {
            for (int it = 0; it < K3_NST; it++) {
                mbar_expect(bar_full + 8 * it, K3_STAGE);
                tma2d(sb + it * K3_STAGE, &tm_wob, bar_full + 8 * it, ct * 64, it * 64);
            }
            TS_MIN(8);
            GRIDDEP_WAIT();
            TS_MIN(9); TS_MAX(18); CK3(1);
            for (int it = 0; it < 20; it++) {
                const int s = it % K3_NST;
                const uint32_t st = sb + s * K3_STAGE, fb = bar_full + 8 * s;
                if (it >= K3_NST) {
                    mbar_wait(bar_empty + 8 * s, ((it / K3_NST) - 1) & 1);
                    mbar_expect(fb, K3_STAGE);
                    tma2d(st, it < 10 ? &tm_wob : &tm_wm, fb, ct * 64, (it % 10) * 64);
                }
                bulk_load(st + 8192, g_acat + (size_t)(((it + 10) % 20) * 256 + tt * 20) * 1024, 20480, fb);
            }
        }
    } else {
        float acc[80];
        #pragma unroll
        for (int i = 0; i < 80; i++) acc[i] = 0.f;
        fence_f(acc);
        for (int it = 0; it < 20; it++) {
            const int s = it % K3_NST;
            mbar_wait(bar_full + 8 * s, (it / K3_NST) & 1);
            if (it == 0) CK3(2); if (it == 6) CK3(3); if (it == 12) CK3(4);
            const uint32_t st = sb + s * K3_STAGE;
            const uint64_t da = mkdesc(st, 8192, 1024, 1), db = mkdesc(st + 8192, 128, 1024, 0);
            WG_FENCE();
            #pragma unroll
            for (int k = 0; k < 4; k++) wg_ss_n160_at(acc, da + k * 128, db + k * 16, 1);
            WG_COMMIT();
            WG_WAIT(1);
            if (it > 0 && lane == 0) mbar_arrive(bar_empty + 8 * ((it - 1) % K3_NST));
        }
        WG_WAIT(0);
        fence_f(acc);
        CK3(5);
        named_bar(1, 128);
        #pragma unroll
        for (int j = 0; j < 20; j += 2) {
            const int tok = 8 * (j + (lane >> 4)) + (lane & 7);
            const int chunk = (2 * warp + ((lane >> 3) & 1)) ^ (tok & 7);
            const uint32_t addr = sb + tok * 128 + chunk * 16;
            asm volatile("stmatrix.sync.aligned.m8n8.x4.trans.shared.b16 [%0], {%1,%2,%3,%4};" :: "r"(addr),
                "r"(packbf(acc[4*j], acc[4*j+1])), "r"(packbf(acc[4*j+2], acc[4*j+3])), "r"(packbf(acc[4*j+4], acc[4*j+5])), "r"(packbf(acc[4*j+6], acc[4*j+7])) : "memory");
        }
        named_bar(1, 128);
        #pragma unroll
        for (int i = 0; i < 10; i++) {
            const int idx = tid + 128 * i, tok = idx >> 3, ch = idx & 7;
            const int gtok = tt * 160 + tok;
            const uint4 v = *(const uint4*)(smem + tok * 128 + ((ch ^ (tok & 7)) * 16));
            if (gtok < SEQ) *(uint4*)(out + (size_t)gtok * DM + ct * 64 + ch * 8) = v;
        }
        TS_MAX(10); CK3(6);
    }
}

typedef CUresult (*PFN_tmapEncode)(CUtensorMap*, CUtensorMapDataType, cuuint32_t, void*, const cuuint64_t*, const cuuint64_t*, const cuuint32_t*, const cuuint32_t*,
                                   CUtensorMapInterleave, CUtensorMapSwizzle, CUtensorMapL2promotion, CUtensorMapFloatOOBfill);
static void make_map(PFN_tmapEncode enc, CUtensorMap* tm, const void* ptr, uint64_t cols, uint64_t rows, uint32_t bcols, uint32_t brows) {
    cuuint64_t gd[2] = {cols, rows}; cuuint64_t gs[1] = {cols * 2}; cuuint32_t bx[2] = {bcols, brows}; cuuint32_t es[2] = {1, 1};
    enc(tm, CU_TENSOR_MAP_DATA_TYPE_BFLOAT16, 2, (void*)ptr, gd, gs, bx, es, CU_TENSOR_MAP_INTERLEAVE_NONE, CU_TENSOR_MAP_SWIZZLE_128B,
        CU_TENSOR_MAP_L2_PROMOTION_L2_128B, CU_TENSOR_MAP_FLOAT_OOB_FILL_NONE);
}

extern "C" void kernel_launch(void* const* d_in, const int* in_sizes, int n_in, void* d_out, int out_size) {
    const __nv_bfloat16* x = (const __nv_bfloat16*)d_in[0];
    const __nv_bfloat16* a_wqkv = (const __nv_bfloat16*)d_in[1];
    const __nv_bfloat16* a_wo = (const __nv_bfloat16*)d_in[2];
    const __nv_bfloat16* b_wqkv = (const __nv_bfloat16*)d_in[4];
    const __nv_bfloat16* b_wo = (const __nv_bfloat16*)d_in[5];
    const __nv_bfloat16* gate_w = (const __nv_bfloat16*)d_in[6];
    static CUtensorMap tm_x, tm_wm, tm_wob;
    static WMaps tm_w;
    static const void* cached[4] = {nullptr, nullptr, nullptr, nullptr};
    if (cached[0] != x || cached[1] != a_wqkv || cached[2] != b_wqkv || cached[3] != b_wo) {
        void* fn = nullptr; cudaDriverEntryPointQueryResult qr;
        cudaGetDriverEntryPoint("cuTensorMapEncodeTiled", &fn, cudaEnableDefault, &qr);
        PFN_tmapEncode enc = (PFN_tmapEncode)fn;
        void* p_wm;
        cudaGetSymbolAddress(&p_wm, g_wm);
        make_map(enc, &tm_x, x, DM, SEQ, 64, 128);
        for (int i = 0; i < 4; i++) {
            cuuint64_t gd[4] = {64, DM, 10, 3}; cuuint64_t gs[3] = {3 * DM * 2, 128, DM * 2};
            cuuint32_t bx[4] = {64, 64, 3, (cuuint32_t)((i & 1) ? 1 : 2)}; cuuint32_t es[4] = {1, 1, 1, 1};
            enc(&tm_w.m[i], CU_TENSOR_MAP_DATA_TYPE_BFLOAT16, 4, (void*)(i < 2 ? a_wqkv : b_wqkv), gd, gs, bx, es, CU_TENSOR_MAP_INTERLEAVE_NONE,
                CU_TENSOR_MAP_SWIZZLE_128B, CU_TENSOR_MAP_L2_PROMOTION_L2_128B, CU_TENSOR_MAP_FLOAT_OOB_FILL_NONE);
        }
        make_map(enc, &tm_wm, p_wm, DM, DM, 64, 64);
        make_map(enc, &tm_wob, b_wo, DM, DM, 64, 64);
        cudaFuncSetAttribute(qkv_kernel, cudaFuncAttributeMaxDynamicSharedMemorySize, K1_SMEM);
        cudaFuncSetAttribute(attn_kernel, cudaFuncAttributeMaxDynamicSharedMemorySize, K2_SMEM);
        cudaFuncSetAttribute(out_kernel, cudaFuncAttributeMaxDynamicSharedMemorySize, K3_SMEM);
        cached[0] = x; cached[1] = a_wqkv; cached[2] = b_wqkv; cached[3] = b_wo;
    }
    cudaStream_t st = cudaStreamPerThread;
    cudaLaunchAttribute at[1];
    at[0].id = cudaLaunchAttributeProgrammaticStreamSerialization; at[0].val.programmaticStreamSerializationAllowed = 1;
    cudaLaunchConfig_t cfg = {};
    cfg.stream = st;
    cfg.gridDim = dim3(128); cfg.blockDim = dim3(512); cfg.dynamicSmemBytes = K1_SMEM; cfg.attrs = at; cfg.numAttrs = 0;
    cudaLaunchKernelEx(&cfg, qkv_kernel, tm_x, tm_w, x, gate_w, a_wo, b_wo);
    cfg.gridDim = dim3(132); cfg.blockDim = dim3(512); cfg.dynamicSmemBytes = K2_SMEM; cfg.numAttrs = 1;
    cudaLaunchKernelEx(&cfg, attn_kernel, a_wo);
    cfg.gridDim = dim3(130); cfg.blockDim = dim3(160); cfg.dynamicSmemBytes = K3_SMEM; cfg.numAttrs = 1;
    cudaLaunchKernelEx(&cfg, out_kernel, tm_wm, tm_wob, (__nv_bfloat16*)d_out);
}
```

```cpp
#include <cuda_runtime.h>
#include <cuda_bf16.h>
#include <cuda.h>
#include <stdint.h>

#define SEQ 2048
#define DM 640
#define NH 32
#define DH 20

#define POLY_MASK 0xD5DDu
#define POLY_DEG 1

__device__ __align__(1024) uint8_t g_kvimg[NH * 196608];
__device__ __align__(1024) uint8_t g_qb[SEQ * DM * 2];
__device__ __align__(1024) uint8_t g_pq[SEQ * DM * 2];
__device__ __align__(1024) uint8_t g_acat[SEQ * 2 * DM * 2 + 4096];
__device__ __align__(1024) __nv_bfloat16 g_wm[DM * DM];
__device__ __align__(16) float g_kvpart[16 * NH * 480];
__device__ __align__(16) float g_zpart[16 * NH * 20];
__device__ __align__(16) float g_kn2[NH * 128];
__device__ __align__(16) float g_gate[SEQ];

__device__ __forceinline__ uint32_t smem_u32(const void* p) { return (uint32_t)__cvta_generic_to_shared(p); }
__device__ __forceinline__ uint64_t mkdesc(uint32_t saddr, uint32_t lbo, uint32_t sbo, uint32_t swz) {
    return (uint64_t)((saddr & 0x3FFFF) >> 4) | ((uint64_t)(lbo >> 4) << 16) | ((uint64_t)(sbo >> 4) << 32) | ((uint64_t)swz << 62);
}
#define WG_FENCE() asm volatile("wgmma.fence.sync.aligned;" ::: "memory")
#define WG_COMMIT() asm volatile("wgmma.commit_group.sync.aligned;" ::: "memory")
#define WG_WAIT(n) asm volatile("wgmma.wait_group.sync.aligned %0;" :: "n"(n) : "memory")
template<int N> __device__ __forceinline__ void fence_f(float (&d)[N]) {
    #pragma unroll
    for (int i = 0; i < N; i++) asm volatile("" : "+f"(d[i]) :: "memory");
}
template<int N> __device__ __forceinline__ void fence_r(uint32_t (&d)[N]) {
    #pragma unroll
    for (int i = 0; i < N; i++) asm volatile("" : "+r"(d[i]) :: "memory");
}
__device__ __forceinline__ void mbar_init(uint32_t bar, uint32_t cnt) { asm volatile("mbarrier.init.shared::cta.b64 [%0], %1;" :: "r"(bar), "r"(cnt)); }
__device__ __forceinline__ void mbar_expect(uint32_t bar, uint32_t bytes) { asm volatile("mbarrier.arrive.expect_tx.shared::cta.b64 _, [%0], %1;" :: "r"(bar), "r"(bytes) : "memory"); }
__device__ __forceinline__ void mbar_arrive(uint32_t bar) { asm volatile("mbarrier.arrive.shared::cta.b64 _, [%0];" :: "r"(bar) : "memory"); }
__device__ __forceinline__ void mbar_wait(uint32_t bar, uint32_t parity) {
    asm volatile("{\n.reg .pred p;\nWAIT_%=:\nmbarrier.try_wait.parity.shared::cta.b64 p, [%0], %1;\n@p bra DONE_%=;\nbra WAIT_%=;\nDONE_%=:\n}" :: "r"(bar), "r"(parity) : "memory");
}
__device__ __forceinline__ void tma2d(uint32_t dst, const CUtensorMap* tm, uint32_t bar, int c0, int c1) {
    asm volatile("cp.async.bulk.tensor.2d.shared::cluster.global.mbarrier::complete_tx::bytes [%0], [%1, {%3,%4}], [%2];"
        :: "r"(dst), "l"((uint64_t)tm), "r"(bar), "r"(c0), "r"(c1) : "memory");
}
__device__ __forceinline__ void bulk_load(uint32_t dst, const void* src, uint32_t bytes, uint32_t bar) {
    asm volatile("cp.async.bulk.shared::cluster.global.mbarrier::complete_tx::bytes [%0], [%1], %2, [%3];" :: "r"(dst), "l"(src), "r"(bytes), "r"(bar) : "memory");
}
__device__ __forceinline__ void l2_prefetch(const void* src, uint32_t bytes) {
    asm volatile("cp.async.bulk.prefetch.L2.global [%0], %1;" :: "l"(src), "r"(bytes) : "memory");
}
__device__ __forceinline__ void named_bar(int id, int n) { asm volatile("bar.sync %0, %1;" :: "r"(id), "r"(n) : "memory"); }
__device__ __forceinline__ float ex2f(float x) { float y; asm("ex2.approx.ftz.f32 %0, %1;" : "=f"(y) : "f"(x)); return y; }
__device__ __forceinline__ uint32_t packbf(float lo, float hi) { uint32_t r; asm("cvt.rn.bf16x2.f32 %0, %1, %2;" : "=r"(r) : "f"(hi), "f"(lo)); return r; }
__device__ __forceinline__ float bflo(uint32_t v) { return __uint_as_float(v << 16); }
__device__ __forceinline__ float bfhi(uint32_t v) { return __uint_as_float(v & 0xFFFF0000u); }
__device__ __forceinline__ float bfr(float v) { return bflo(packbf(v, 0.f)); }
__device__ __forceinline__ float dot_bf(uint32_t a, uint32_t b) {
    uint32_t p; asm("mul.rn.bf16x2 %0, %1, %2;" : "=r"(p) : "r"(a), "r"(b));
    return bflo(p) + bfhi(p);
}
__device__ __forceinline__ float phi_f(float t) { return (fmaxf(t, 0.f) + 1e-6f) + ex2f(fminf(t, 0.f) * 1.4426950408889634f); }
__device__ __forceinline__ uint32_t q_off(int tok, int col) { return ((tok >> 3) * 80 + (col >> 3)) * 128 + (tok & 7) * 16 + (col & 7) * 2; }
__device__ __forceinline__ uint32_t acat_off(int tok, int kk) { return (((kk >> 6) * 256 + (tok >> 3)) * 8 + ((kk >> 3) & 7)) * 128 + (tok & 7) * 16 + (kk & 7) * 2; }
#define GRIDDEP_WAIT() asm volatile("griddepcontrol.wait;" ::: "memory")
#define GRIDDEP_LAUNCH() asm volatile("griddepcontrol.launch_dependents;" ::: "memory")

#define TS_MIN(i)
#define CK(k, i)
#define CK3(i)
#define TS_MAX(i)

__device__ __forceinline__ void wg_rs_n128_bt(float (&d)[64], uint32_t a0, uint32_t a1, uint32_t a2, uint32_t a3, uint64_t db) {
    asm volatile("wgmma.mma_async.sync.aligned.m64n128k16.f32.bf16.bf16 {%0,%1,%2,%3,%4,%5,%6,%7,%8,%9,%10,%11,%12,%13,%14,%15,%16,%17,%18,%19,%20,%21,%22,%23,%24,%25,%26,%27,%28,%29,%30,%31,%32,%33,%34,%35,%36,%37,%38,%39,%40,%41,%42,%43,%44,%45,%46,%47,%48,%49,%50,%51,%52,%53,%54,%55,%56,%57,%58,%59,%60,%61,%62,%63}, {%64,%65,%66,%67}, %68, 1, 1, 1, 1;"
      : "+f"(d[0]),"+f"(d[1]),"+f"(d[2]),"+f"(d[3]),"+f"(d[4]),"+f"(d[5]),"+f"(d[6]),"+f"(d[7]),"+f"(d[8]),"+f"(d[9]),"+f"(d[10]),"+f"(d[11]),"+f"(d[12]),"+f"(d[13]),"+f"(d[14]),"+f"(d[15]),"+f"(d[16]),"+f"(d[17]),"+f"(d[18]),"+f"(d[19]),"+f"(d[20]),"+f"(d[21]),"+f"(d[22]),"+f"(d[23]),"+f"(d[24]),"+f"(d[25]),"+f"(d[26]),"+f"(d[27]),"+f"(d[28]),"+f"(d[29]),"+f"(d[30]),"+f"(d[31]),"+f"(d[32]),"+f"(d[33]),"+f"(d[34]),"+f"(d[35]),"+f"(d[36]),"+f"(d[37]),"+f"(d[38]),"+f"(d[39]),"+f"(d[40]),"+f"(d[41]),"+f"(d[42]),"+f"(d[43]),"+f"(d[44]),"+f"(d[45]),"+f"(d[46]),"+f"(d[47]),"+f"(d[48]),"+f"(d[49]),"+f"(d[50]),"+f"(d[51]),"+f"(d[52]),"+f"(d[53]),"+f"(d[54]),"+f"(d[55]),"+f"(d[56]),"+f"(d[57]),"+f"(d[58]),"+f"(d[59]),"+f"(d[60]),"+f"(d[61]),"+f"(d[62]),"+f"(d[63]) : "r"(a0), "r"(a1), "r"(a2), "r"(a3), "l"(db));
}
__device__ __forceinline__ void wg_ss_n64_bt(float (&d)[32], uint64_t da, uint64_t db, int acc) {
    asm volatile("{.reg .pred p; setp.ne.b32 p, %34, 0;\n"
      "wgmma.mma_async.sync.aligned.m64n64k16.f32.bf16.bf16 {%0,%1,%2,%3,%4,%5,%6,%7,%8,%9,%10,%11,%12,%13,%14,%15,%16,%17,%18,%19,%20,%21,%22,%23,%24,%25,%26,%27,%28,%29,%30,%31}, %32, %33, p, 1, 1, 0, 1;}"
      : "+f"(d[0]),"+f"(d[1]),"+f"(d[2]),"+f"(d[3]),"+f"(d[4]),"+f"(d[5]),"+f"(d[6]),"+f"(d[7]),"+f"(d[8]),"+f"(d[9]),"+f"(d[10]),"+f"(d[11]),"+f"(d[12]),"+f"(d[13]),"+f"(d[14]),"+f"(d[15]),"+f"(d[16]),"+f"(d[17]),"+f"(d[18]),"+f"(d[19]),"+f"(d[20]),"+f"(d[21]),"+f"(d[22]),"+f"(d[23]),"+f"(d[24]),"+f"(d[25]),"+f"(d[26]),"+f"(d[27]),"+f"(d[28]),"+f"(d[29]),"+f"(d[30]),"+f"(d[31]) : "l"(da), "l"(db), "r"(acc));
}
__device__ __forceinline__ void wg_ss_n32_bt(float (&d)[16], uint64_t da, uint64_t db, int acc) {
    asm volatile("{.reg .pred p; setp.ne.b32 p, %18, 0;\n"
      "wgmma.mma_async.sync.aligned.m64n32k16.f32.bf16.bf16 {%0,%1,%2,%3,%4,%5,%6,%7,%8,%9,%10,%11,%12,%13,%14,%15}, %16, %17, p, 1, 1, 0, 1;}"
      : "+f"(d[0]),"+f"(d[1]),"+f"(d[2]),"+f"(d[3]),"+f"(d[4]),"+f"(d[5]),"+f"(d[6]),"+f"(d[7]),"+f"(d[8]),"+f"(d[9]),"+f"(d[10]),"+f"(d[11]),"+f"(d[12]),"+f"(d[13]),"+f"(d[14]),"+f"(d[15]) : "l"(da), "l"(db), "r"(acc));
}
__device__ __forceinline__ void wg_rs_n32_bt(float (&d)[16], uint32_t a0, uint32_t a1, uint32_t a2, uint32_t a3, uint64_t db) {
    asm volatile("wgmma.mma_async.sync.aligned.m64n32k16.f32.bf16.bf16 {%0,%1,%2,%3,%4,%5,%6,%7,%8,%9,%10,%11,%12,%13,%14,%15}, {%16,%17,%18,%19}, %20, 1, 1, 1, 1;"
      : "+f"(d[0]),"+f"(d[1]),"+f"(d[2]),"+f"(d[3]),"+f"(d[4]),"+f"(d[5]),"+f"(d[6]),"+f"(d[7]),"+f"(d[8]),"+f"(d[9]),"+f"(d[10]),"+f"(d[11]),"+f"(d[12]),"+f"(d[13]),"+f"(d[14]),"+f"(d[15]) : "r"(a0), "r"(a1), "r"(a2), "r"(a3), "l"(db));
}
__device__ __forceinline__ void wg_ss_n88_atbt(float (&d)[44], uint64_t da, uint64_t db, int acc) {
    asm volatile("{.reg .pred p; setp.ne.b32 p, %46, 0;\n"
      "wgmma.mma_async.sync.aligned.m64n88k16.f32.bf16.bf16 {%0,%1,%2,%3,%4,%5,%6,%7,%8,%9,%10,%11,%12,%13,%14,%15,%16,%17,%18,%19,%20,%21,%22,%23,%24,%25,%26,%27,%28,%29,%30,%31,%32,%33,%34,%35,%36,%37,%38,%39,%40,%41,%42,%43}, %44, %45, p, 1, 1, 1, 1;}"
      : "+f"(d[0]),"+f"(d[1]),"+f"(d[2]),"+f"(d[3]),"+f"(d[4]),"+f"(d[5]),"+f"(d[6]),"+f"(d[7]),"+f"(d[8]),"+f"(d[9]),"+f"(d[10]),"+f"(d[11]),"+f"(d[12]),"+f"(d[13]),"+f"(d[14]),"+f"(d[15]),"+f"(d[16]),"+f"(d[17]),"+f"(d[18]),"+f"(d[19]),"+f"(d[20]),"+f"(d[21]),"+f"(d[22]),"+f"(d[23]),"+f"(d[24]),"+f"(d[25]),"+f"(d[26]),"+f"(d[27]),"+f"(d[28]),"+f"(d[29]),"+f"(d[30]),"+f"(d[31]),"+f"(d[32]),"+f"(d[33]),"+f"(d[34]),"+f"(d[35]),"+f"(d[36]),"+f"(d[37]),"+f"(d[38]),"+f"(d[39]),"+f"(d[40]),"+f"(d[41]),"+f"(d[42]),"+f"(d[43]) : "l"(da), "l"(db), "r"(acc));
}
__device__ __forceinline__ void wg_ss_n8_atbt(float (&d)[4], uint64_t da, uint64_t db, int acc) {
    asm volatile("{.reg .pred p; setp.ne.b32 p, %6, 0;\n"
      "wgmma.mma_async.sync.aligned.m64n8k16.f32.bf16.bf16 {%0,%1,%2,%3}, %4, %5, p, 1, 1, 1, 1;}"
      : "+f"(d[0]),"+f"(d[1]),"+f"(d[2]),"+f"(d[3]) : "l"(da), "l"(db), "r"(acc));
}
__device__ __forceinline__ void wg_ss_n160_at(float (&d)[80], uint64_t da, uint64_t db, int acc) {
    asm volatile("{.reg .pred p; setp.ne.b32 p, %82, 0;\n"
      "wgmma.mma_async.sync.aligned.m64n160k16.f32.bf16.bf16 {%0,%1,%2,%3,%4,%5,%6,%7,%8,%9,%10,%11,%12,%13,%14,%15,%16,%17,%18,%19,%20,%21,%22,%23,%24,%25,%26,%27,%28,%29,%30,%31,%32,%33,%34,%35,%36,%37,%38,%39,%40,%41,%42,%43,%44,%45,%46,%47,%48,%49,%50,%51,%52,%53,%54,%55,%56,%57,%58,%59,%60,%61,%62,%63,%64,%65,%66,%67,%68,%69,%70,%71,%72,%73,%74,%75,%76,%77,%78,%79}, %80, %81, p, 1, 1, 1, 0;}"
      : "+f"(d[0]),"+f"(d[1]),"+f"(d[2]),"+f"(d[3]),"+f"(d[4]),"+f"(d[5]),"+f"(d[6]),"+f"(d[7]),"+f"(d[8]),"+f"(d[9]),"+f"(d[10]),"+f"(d[11]),"+f"(d[12]),"+f"(d[13]),"+f"(d[14]),"+f"(d[15]),"+f"(d[16]),"+f"(d[17]),"+f"(d[18]),"+f"(d[19]),"+f"(d[20]),"+f"(d[21]),"+f"(d[22]),"+f"(d[23]),"+f"(d[24]),"+f"(d[25]),"+f"(d[26]),"+f"(d[27]),"+f"(d[28]),"+f"(d[29]),"+f"(d[30]),"+f"(d[31]),"+f"(d[32]),"+f"(d[33]),"+f"(d[34]),"+f"(d[35]),"+f"(d[36]),"+f"(d[37]),"+f"(d[38]),"+f"(d[39]),"+f"(d[40]),"+f"(d[41]),"+f"(d[42]),"+f"(d[43]),"+f"(d[44]),"+f"(d[45]),"+f"(d[46]),"+f"(d[47]),"+f"(d[48]),"+f"(d[49]),"+f"(d[50]),"+f"(d[51]),"+f"(d[52]),"+f"(d[53]),"+f"(d[54]),"+f"(d[55]),"+f"(d[56]),"+f"(d[57]),"+f"(d[58]),"+f"(d[59]),"+f"(d[60]),"+f"(d[61]),"+f"(d[62]),"+f"(d[63]),"+f"(d[64]),"+f"(d[65]),"+f"(d[66]),"+f"(d[67]),"+f"(d[68]),"+f"(d[69]),"+f"(d[70]),"+f"(d[71]),"+f"(d[72]),"+f"(d[73]),"+f"(d[74]),"+f"(d[75]),"+f"(d[76]),"+f"(d[77]),"+f"(d[78]),"+f"(d[79]) : "l"(da), "l"(db), "r"(acc));
}
__device__ __forceinline__ void wg_qk0(float (&d)[32], uint32_t a0, uint32_t a1, uint32_t a2, uint32_t a3, uint64_t db) {
    asm volatile("wgmma.mma_async.sync.aligned.m64n64k16.f32.bf16.bf16 {%0,%1,%2,%3,%4,%5,%6,%7,%8,%9,%10,%11,%12,%13,%14,%15,%16,%17,%18,%19,%20,%21,%22,%23,%24,%25,%26,%27,%28,%29,%30,%31}, {%32,%33,%34,%35}, %36, 0, 1, 1, 0;"
      : "+f"(d[0]),"+f"(d[1]),"+f"(d[2]),"+f"(d[3]),"+f"(d[4]),"+f"(d[5]),"+f"(d[6]),"+f"(d[7]),"+f"(d[8]),"+f"(d[9]),"+f"(d[10]),"+f"(d[11]),"+f"(d[12]),"+f"(d[13]),"+f"(d[14]),"+f"(d[15]),"+f"(d[16]),"+f"(d[17]),"+f"(d[18]),"+f"(d[19]),"+f"(d[20]),"+f"(d[21]),"+f"(d[22]),"+f"(d[23]),"+f"(d[24]),"+f"(d[25]),"+f"(d[26]),"+f"(d[27]),"+f"(d[28]),"+f"(d[29]),"+f"(d[30]),"+f"(d[31]) : "r"(a0), "r"(a1), "r"(a2), "r"(a3), "l"(db));
}
__device__ __forceinline__ void wg_qk1(float (&d)[32], uint32_t a0, uint32_t a1, uint32_t a2, uint32_t a3, uint64_t db) {
    asm volatile("wgmma.mma_async.sync.aligned.m64n64k16.f32.bf16.bf16 {%0,%1,%2,%3,%4,%5,%6,%7,%8,%9,%10,%11,%12,%13,%14,%15,%16,%17,%18,%19,%20,%21,%22,%23,%24,%25,%26,%27,%28,%29,%30,%31}, {%32,%33,%34,%35}, %36, 1, 1, 1, 0;"
      : "+f"(d[0]),"+f"(d[1]),"+f"(d[2]),"+f"(d[3]),"+f"(d[4]),"+f"(d[5]),"+f"(d[6]),"+f"(d[7]),"+f"(d[8]),"+f"(d[9]),"+f"(d[10]),"+f"(d[11]),"+f"(d[12]),"+f"(d[13]),"+f"(d[14]),"+f"(d[15]),"+f"(d[16]),"+f"(d[17]),"+f"(d[18]),"+f"(d[19]),"+f"(d[20]),"+f"(d[21]),"+f"(d[22]),"+f"(d[23]),"+f"(d[24]),"+f"(d[25]),"+f"(d[26]),"+f"(d[27]),"+f"(d[28]),"+f"(d[29]),"+f"(d[30]),"+f"(d[31]) : "r"(a0), "r"(a1), "r"(a2), "r"(a3), "l"(db));
}
__device__ __forceinline__ void wg_qk0w(float (&d)[64], uint32_t a0, uint32_t a1, uint32_t a2, uint32_t a3, uint64_t db) {
    asm volatile("wgmma.mma_async.sync.aligned.m64n128k16.f32.bf16.bf16 {%0,%1,%2,%3,%4,%5,%6,%7,%8,%9,%10,%11,%12,%13,%14,%15,%16,%17,%18,%19,%20,%21,%22,%23,%24,%25,%26,%27,%28,%29,%30,%31,%32,%33,%34,%35,%36,%37,%38,%39,%40,%41,%42,%43,%44,%45,%46,%47,%48,%49,%50,%51,%52,%53,%54,%55,%56,%57,%58,%59,%60,%61,%62,%63}, {%64,%65,%66,%67}, %68, 0, 1, 1, 0;"
      : "+f"(d[0]),"+f"(d[1]),"+f"(d[2]),"+f"(d[3]),"+f"(d[4]),"+f"(d[5]),"+f"(d[6]),"+f"(d[7]),"+f"(d[8]),"+f"(d[9]),"+f"(d[10]),"+f"(d[11]),"+f"(d[12]),"+f"(d[13]),"+f"(d[14]),"+f"(d[15]),"+f"(d[16]),"+f"(d[17]),"+f"(d[18]),"+f"(d[19]),"+f"(d[20]),"+f"(d[21]),"+f"(d[22]),"+f"(d[23]),"+f"(d[24]),"+f"(d[25]),"+f"(d[26]),"+f"(d[27]),"+f"(d[28]),"+f"(d[29]),"+f"(d[30]),"+f"(d[31]),"+f"(d[32]),"+f"(d[33]),"+f"(d[34]),"+f"(d[35]),"+f"(d[36]),"+f"(d[37]),"+f"(d[38]),"+f"(d[39]),"+f"(d[40]),"+f"(d[41]),"+f"(d[42]),"+f"(d[43]),"+f"(d[44]),"+f"(d[45]),"+f"(d[46]),"+f"(d[47]),"+f"(d[48]),"+f"(d[49]),"+f"(d[50]),"+f"(d[51]),"+f"(d[52]),"+f"(d[53]),"+f"(d[54]),"+f"(d[55]),"+f"(d[56]),"+f"(d[57]),"+f"(d[58]),"+f"(d[59]),"+f"(d[60]),"+f"(d[61]),"+f"(d[62]),"+f"(d[63]) : "r"(a0), "r"(a1), "r"(a2), "r"(a3), "l"(db));
}
__device__ __forceinline__ void wg_qk1w(float (&d)[64], uint32_t a0, uint32_t a1, uint32_t a2, uint32_t a3, uint64_t db) {
    asm volatile("wgmma.mma_async.sync.aligned.m64n128k16.f32.bf16.bf16 {%0,%1,%2,%3,%4,%5,%6,%7,%8,%9,%10,%11,%12,%13,%14,%15,%16,%17,%18,%19,%20,%21,%22,%23,%24,%25,%26,%27,%28,%29,%30,%31,%32,%33,%34,%35,%36,%37,%38,%39,%40,%41,%42,%43,%44,%45,%46,%47,%48,%49,%50,%51,%52,%53,%54,%55,%56,%57,%58,%59,%60,%61,%62,%63}, {%64,%65,%66,%67}, %68, 1, 1, 1, 0;"
      : "+f"(d[0]),"+f"(d[1]),"+f"(d[2]),"+f"(d[3]),"+f"(d[4]),"+f"(d[5]),"+f"(d[6]),"+f"(d[7]),"+f"(d[8]),"+f"(d[9]),"+f"(d[10]),"+f"(d[11]),"+f"(d[12]),"+f"(d[13]),"+f"(d[14]),"+f"(d[15]),"+f"(d[16]),"+f"(d[17]),"+f"(d[18]),"+f"(d[19]),"+f"(d[20]),"+f"(d[21]),"+f"(d[22]),"+f"(d[23]),"+f"(d[24]),"+f"(d[25]),"+f"(d[26]),"+f"(d[27]),"+f"(d[28]),"+f"(d[29]),"+f"(d[30]),"+f"(d[31]),"+f"(d[32]),"+f"(d[33]),"+f"(d[34]),"+f"(d[35]),"+f"(d[36]),"+f"(d[37]),"+f"(d[38]),"+f"(d[39]),"+f"(d[40]),"+f"(d[41]),"+f"(d[42]),"+f"(d[43]),"+f"(d[44]),"+f"(d[45]),"+f"(d[46]),"+f"(d[47]),"+f"(d[48]),"+f"(d[49]),"+f"(d[50]),"+f"(d[51]),"+f"(d[52]),"+f"(d[53]),"+f"(d[54]),"+f"(d[55]),"+f"(d[56]),"+f"(d[57]),"+f"(d[58]),"+f"(d[59]),"+f"(d[60]),"+f"(d[61]),"+f"(d[62]),"+f"(d[63]) : "r"(a0), "r"(a1), "r"(a2), "r"(a3), "l"(db));
}
__device__ __forceinline__ void wg_pv(float (&d)[12], uint32_t a0, uint32_t a1, uint32_t a2, uint32_t a3, uint64_t db) {
    asm volatile("wgmma.mma_async.sync.aligned.m64n24k16.f32.bf16.bf16 {%0,%1,%2,%3,%4,%5,%6,%7,%8,%9,%10,%11}, {%12,%13,%14,%15}, %16, 1, 1, 1, 1;"
      : "+f"(d[0]),"+f"(d[1]),"+f"(d[2]),"+f"(d[3]),"+f"(d[4]),"+f"(d[5]),"+f"(d[6]),"+f"(d[7]),"+f"(d[8]),"+f"(d[9]),"+f"(d[10]),"+f"(d[11]) : "r"(a0), "r"(a1), "r"(a2), "r"(a3), "l"(db));
}

#define K1_ONES 204800
#define K1_BARS 205056
#define K1_SMEM 205312
#define QSCALE 0.32259799f
#define K1_BAR(i) (sb + K1_BARS + 8 * (i))

__device__ __forceinline__ void tma4d(uint32_t dst, const CUtensorMap* tm, uint32_t bar, int c0, int c1, int c2, int c3) {
    asm volatile("cp.async.bulk.tensor.4d.shared::cluster.global.mbarrier::complete_tx::bytes [%0], [%1, {%3,%4,%5,%6}], [%2];"
        :: "r"(dst), "l"((uint64_t)tm), "r"(bar), "r"(c0), "r"(c1), "r"(c2), "r"(c3) : "memory");
}
__device__ __forceinline__ void k1_issue(int pass, int kb, uint32_t sb, const CUtensorMap* tx, const CUtensorMap* tw, int mt, int hg) {
    const int s = pass ? kb % 5 : kb % 3;
    const uint32_t st = sb + (pass ? s * 40960 : s * 65536), fb = K1_BAR(pass ? s : 10 + s);
    mbar_expect(fb, pass ? 40960 : 65536);
    tma2d(st, tx, fb, kb * 64, mt * 128);
    tma4d(st + 16384, tw + pass, fb, 0, kb * 64, (hg * 160) >> 6, 1 - pass);
}
__device__ __forceinline__ void stsm4(uint32_t addr, uint32_t r0, uint32_t r1, uint32_t r2, uint32_t r3) {
    asm volatile("stmatrix.sync.aligned.m8n8.x4.shared.b16 [%0], {%1,%2,%3,%4};" :: "r"(addr), "r"(r0), "r"(r1), "r"(r2), "r"(r3) : "memory");
}
__device__ __forceinline__ void bulk_store(void* dst, uint32_t src, uint32_t bytes) {
    asm volatile("cp.async.bulk.global.shared::cta.bulk_group [%0], [%1], %2;" :: "l"(dst), "r"(src), "r"(bytes) : "memory");
}
#define FENCE_ASYNC() asm volatile("fence.proxy.async.shared::cta;" ::: "memory")

__device__ __forceinline__ void k1_stage_rows(const uint32_t (&pk)[40], uint32_t base, bool odd) {
    const uint32_t b0 = base + (odd ? 512 : 0), b2 = base + (odd ? 0 : 2048);
    #pragma unroll
    for (int j = 0; j < 16; j += 2) stsm4(b0 + j * 128, pk[2*j], pk[2*j+1], pk[2*j+2], pk[2*j+3]);
    #pragma unroll
    for (int j = 0; j < 4; j += 2) stsm4(b2 + j * 128, pk[32 + 2*j], pk[33 + 2*j], pk[34 + 2*j], pk[35 + 2*j]);
}
template<bool ODD>
__device__ __forceinline__ void k1_image(const uint32_t (&pk)[40], uint32_t base, int lane) {
    #define PH(j) (ODD ? ((j) < 4 ? (j) + 16 : (j) - 4) : (j))
    const bool hi = lane & 16;
    #pragma unroll
    for (int i = 0; i < 4; i++) {
        const uint32_t e = base + (2 * i) * 12288, o = e + 12288;
        const int j = 5 * i;
        stsm4(hi ? e + 128 : e, pk[2*PH(j)], pk[2*PH(j)+1], pk[2*PH(j+1)], pk[2*PH(j+1)+1]);
        stsm4(hi ? o : e + 256, pk[2*PH(j+2)], pk[2*PH(j+2)+1], pk[2*PH(j+2)], pk[2*PH(j+2)+1]);
        stsm4(hi ? o + 256 : o + 128, pk[2*PH(j+3)], pk[2*PH(j+3)+1], pk[2*PH(j+4)], pk[2*PH(j+4)+1]);
    }
}
template<bool ODD>
__device__ __forceinline__ void k1_norms(const uint32_t (&pk)[40], int lane, float* kn_dst) {
    {
        const bool lo = (lane & 3) < 2;
        #pragma unroll
        for (int h = 0; h < 8; h++) {
            float a = 0.f, b = 0.f;
            #pragma unroll
            for (int jj = 0; jj < 3; jj++) {
                const int j = (5 * h) / 2 + jj;
                const uint32_t v0 = pk[2*PH(j)], v1 = pk[2*PH(j)+1];
                float s0 = bflo(v0) * bflo(v0) + bfhi(v0) * bfhi(v0), s1 = bflo(v1) * bflo(v1) + bfhi(v1) * bfhi(v1);
                if (jj == ((h & 1) ? 0 : 2)) { const bool mine = (h & 1) ? !lo : lo; s0 = mine ? s0 : 0.f; s1 = mine ? s1 : 0.f; }
                a += s0; b += s1;
            }
            a += __shfl_xor_sync(0xffffffffu, a, 1); b += __shfl_xor_sync(0xffffffffu, b, 1);
            a += __shfl_xor_sync(0xffffffffu, a, 2); b += __shfl_xor_sync(0xffffffffu, b, 2);
            a = fmaxf(a, b);
            a = fmaxf(a, __shfl_xor_sync(0xffffffffu, a, 4));
            a = fmaxf(a, __shfl_xor_sync(0xffffffffu, a, 8));
            a = fmaxf(a, __shfl_xor_sync(0xffffffffu, a, 16));
            if (lane == h) kn_dst[h * 128] = a;
        }
    }
    #undef PH
}

struct WMaps { CUtensorMap m[4]; };
__global__ void __launch_bounds__(512, 1)
qkv_kernel(const __grid_constant__ CUtensorMap tm_x, const __grid_constant__ WMaps tm_w,
           const __nv_bfloat16* __restrict__ x, const __nv_bfloat16* __restrict__ gate_w,
           const __nv_bfloat16* __restrict__ woa, const __nv_bfloat16* __restrict__ wob) {
    extern __shared__ __align__(1024) uint8_t smem[];
    const uint32_t sb = smem_u32(smem);
    const int tid = threadIdx.x, warp = tid >> 5, lane = tid & 31;
    const int mt = ((blockIdx.x >> 4) & 3) * 4 + (blockIdx.x & 3), grp = (blockIdx.x >> 6) * 4 + ((blockIdx.x >> 2) & 3), br = grp >> 2, hg = grp & 3;
    const CUtensorMap* tw = &tm_w.m[br * 2];
    TS_MIN(0); CK(0, 0);
    if (tid == 0) {
        for (int i = 0; i < 5; i++) { mbar_init(K1_BAR(i), 1); mbar_init(K1_BAR(5 + i), 16); }
        for (int i = 0; i < 3; i++) { mbar_init(K1_BAR(10 + i), 1); mbar_init(K1_BAR(13 + i), 16); }
        mbar_init(K1_BAR(16), 16); mbar_init(K1_BAR(17), 16); mbar_init(K1_BAR(18), 12);
        asm volatile("fence.mbarrier_init.release.cluster;" ::: "memory");
        k1_issue(1, 0, sb, &tm_x, tw, mt, hg);
    }
    __syncthreads();
    GRIDDEP_LAUNCH();
    if (tid == 0) for (int i = 1; i < 5; i++) k1_issue(1, i, sb, &tm_x, tw, mt, hg);
    if (tid == 32) {
        l2_prefetch(woa + blockIdx.x * 5 * DM, 6400);
        l2_prefetch(wob + blockIdx.x * 5 * DM, 6400);
    }
    if (tid >= 64 && tid < 96) *(uint32_t*)(smem + K1_ONES + lane * 4) = (lane & 3) == 0 ? 0x3F80u : 0u;
    __syncwarp();
    const int wg = __shfl_sync(0xffffffffu, warp >> 2, 0), mh = wg & 1, sel = wg >> 1, w4 = warp & 3;
    const int g = lane >> 2, t = lane & 3;
    const bool odd = hg & 1;
    CK(0, 1);
    {
        float a0[32], a2[16];
        #pragma unroll
        for (int i = 0; i < 32; i++) a0[i] = 0.f;
        #pragma unroll
        for (int i = 0; i < 16; i++) a2[i] = 0.f;
        fence_f(a0); fence_f(a2);
        const uint32_t o0 = sel ? 512 : (odd ? 1024 : 0), o2 = odd ? 4 : 1024;
        for (int kb = 0; kb < 10; kb++) {
            const int s = kb % 5;
            mbar_wait(K1_BAR(s), kb >= 5);
            const uint32_t st = sb + s * 40960;
            const uint64_t da = mkdesc(st + mh * 8192, 16, 1024, 1), db = mkdesc(st + 16384, 8192, 1024, 1);
            WG_FENCE();
            #pragma unroll
            for (int k = 0; k < 4; k++) wg_ss_n64_bt(a0, da + k * 2, db + o0 + k * 128, 1);
            if (sel) {
                #pragma unroll
                for (int k = 0; k < 4; k++) wg_ss_n32_bt(a2, da + k * 2, db + o2 + k * 128, 1);
            }
            WG_COMMIT();
            WG_WAIT(0);
            if (lane == 0) mbar_arrive(K1_BAR(5 + s));
            if (tid == 0) {
                mbar_wait(K1_BAR(5 + s), kb >= 5);
                if (kb < 5) k1_issue(1, kb + 5, sb, &tm_x, tw, mt, hg);
                else if (kb == 6) k1_issue(0, 0, sb, &tm_x, tw, mt, hg);
                else if (kb >= 8) k1_issue(0, kb - 7, sb, &tm_x, tw, mt, hg);
            }
            __syncwarp();
        }
        fence_f(a0); fence_f(a2);
        CK(0, 2);
        uint8_t* dst = (br ? g_qb : g_pq) + ((mt * 16 + mh * 8 + w4 * 2) * 80 + hg * 20) * 128 + lane * 4;
        uint8_t* d0 = dst + (sel ? (odd ? 4 : 8) : (odd ? 12 : 0)) * 128;
        uint8_t* d2 = dst + (odd ? 0 : 16) * 128;
        if (br) {
            #pragma unroll
            for (int j = 0; j < 8; j++) {
                *(uint32_t*)(d0 + j * 128) = packbf(a0[4*j] * QSCALE, a0[4*j+1] * QSCALE);
                *(uint32_t*)(d0 + 10240 + j * 128) = packbf(a0[4*j+2] * QSCALE, a0[4*j+3] * QSCALE);
            }
            if (sel) {
                #pragma unroll
                for (int j = 0; j < 4; j++) {
                    *(uint32_t*)(d2 + j * 128) = packbf(a2[4*j] * QSCALE, a2[4*j+1] * QSCALE);
                    *(uint32_t*)(d2 + 10240 + j * 128) = packbf(a2[4*j+2] * QSCALE, a2[4*j+3] * QSCALE);
                }
            }
        } else {
            #pragma unroll
            for (int j = 0; j < 8; j++) {
                *(uint32_t*)(d0 + j * 128) = packbf(phi_f(a0[4*j]), phi_f(a0[4*j+1]));
                *(uint32_t*)(d0 + 10240 + j * 128) = packbf(phi_f(a0[4*j+2]), phi_f(a0[4*j+3]));
            }
            if (sel) {
                #pragma unroll
                for (int j = 0; j < 4; j++) {
                    *(uint32_t*)(d2 + j * 128) = packbf(phi_f(a2[4*j]), phi_f(a2[4*j+1]));
                    *(uint32_t*)(d2 + 10240 + j * 128) = packbf(phi_f(a2[4*j+2]), phi_f(a2[4*j+3]));
                }
            }
        }
    }
    CK(0, 3);
    uint32_t pk[40];
    {
        float a0[64], a2[16];
        #pragma unroll
        for (int i = 0; i < 64; i++) a0[i] = 0.f;
        #pragma unroll
        for (int i = 0; i < 16; i++) a2[i] = 0.f;
        fence_f(a0); fence_f(a2);
        const uint32_t o0 = odd ? 512 : 0, o2 = odd ? 4 : 1024;
        const uint32_t arow = (mh * 64 + w4 * 16 + (lane & 15)) * 128;
        for (int kb = 0; kb < 10; kb++) {
            const int s = kb % 3;
            mbar_wait(K1_BAR(10 + s), (kb / 3) & 1);
            const uint32_t st = sb + s * 65536;
            const uint64_t db = mkdesc(st + 16384 + sel * 24576, 8192, 1024, 1);
            uint32_t af[4][4];
            #pragma unroll
            for (int k = 0; k < 4; k++)
                asm volatile("ldmatrix.sync.aligned.m8n8.x4.shared.b16 {%0,%1,%2,%3}, [%4];"
                    : "=r"(af[k][0]), "=r"(af[k][1]), "=r"(af[k][2]), "=r"(af[k][3]) : "r"(st + arow + (((2 * k + (lane >> 4)) ^ (lane & 7)) << 4)));
            WG_FENCE();
            #pragma unroll
            for (int k = 0; k < 4; k++) {
                wg_rs_n128_bt(a0, af[k][0], af[k][1], af[k][2], af[k][3], db + o0 + k * 128);
                wg_rs_n32_bt(a2, af[k][0], af[k][1], af[k][2], af[k][3], db + o2 + k * 128);
            }
            WG_COMMIT();
            WG_WAIT(0);
            const uint32_t eb = K1_BAR(kb == 9 ? 16 : 13 + s);
            if (lane == 0) mbar_arrive(eb);
            if (tid == 0 && kb < 7) { mbar_wait(eb, (kb / 3) & 1); k1_issue(0, kb + 3, sb, &tm_x, tw, mt, hg); }
            __syncwarp();
        }
        fence_f(a0); fence_f(a2);
        CK(0, 4);
        if (br == 0 && sel == 0) {
            #pragma unroll
            for (int i = 0; i < 32; i++) pk[i] = packbf(phi_f(a0[2 * i]), phi_f(a0[2 * i + 1]));
            #pragma unroll
            for (int i = 0; i < 8; i++) pk[32 + i] = packbf(phi_f(a2[2 * i]), phi_f(a2[2 * i + 1]));
        } else {
            #pragma unroll
            for (int i = 0; i < 32; i++) pk[i] = packbf(a0[2 * i], a0[2 * i + 1]);
            #pragma unroll
            for (int i = 0; i < 8; i++) pk[32 + i] = packbf(a2[2 * i], a2[2 * i + 1]);
        }
    }
    const int rg = mh * 8 + w4 * 2 + ((lane >> 3) & 1);
    mbar_wait(K1_BAR(14), 0); mbar_wait(K1_BAR(15), 0);
    const uint32_t stg = sb + 65536;
    bool do_gate;
    if (br) {
        const uint32_t base = stg + rg * 768 + sel * 384 + (lane & 7) * 16;
        if (odd) k1_image<true>(pk, base, lane); else k1_image<false>(pk, base, lane);
        __syncwarp();
        {
            const int lr = mh * 64 + w4 * 16 + (lane & 15);
            const uint32_t flag = (sel == 0 && ((POLY_MASK >> ((lr >> 3) & 15)) & 1)) ? 0x3F80u : 0u;
            const uint2 cv = make_uint2(0x3F80u | (flag << 16), flag);
            uint8_t* p = smem + 65536 + (lane >> 4) * 49152 + (lr >> 3) * 768 + sel * 384 + (lr & 7) * 16;
            *(uint2*)(p + 264) = cv; *(uint2*)(p + 12288) = cv; *(uint2*)(p + 24576 + 264) = cv; *(uint2*)(p + 36864) = cv;
        }
        FENCE_ASYNC();
        __syncwarp();
        if (lane == 0) mbar_arrive(K1_BAR(17));
        if (warp == 8 && lane < 8) {
            mbar_wait(K1_BAR(17), 0);
            bulk_store(g_kvimg + (size_t)(hg * 8 + lane) * 196608 + mt * 12288, stg + lane * 12288, 12288);
            asm volatile("cp.async.bulk.commit_group;" ::: "memory");
        }
        __syncwarp();
        if (sel == 0) {
            float* kd = g_kn2 + (hg * 8) * 128 + mt * 8 + mh * 4 + w4;
            if (odd) k1_norms<true>(pk, lane, kd); else k1_norms<false>(pk, lane, kd);
        }
        do_gate = sel == 1;
    } else {
        k1_stage_rows(pk, stg + rg * 5120 + sel * 2560 + (lane >> 4) * 128 + (lane & 7) * 16, odd);
        FENCE_ASYNC();
        __syncwarp();
        if (lane == 0) mbar_arrive(K1_BAR(17));
        if (wg != 0) {
            const int mi = wg - 1;
            mbar_wait(K1_BAR(17), 0);
            float* kvo = (float*)(smem + 65536 + 81920);
            float kv[44], zz[4];
            #pragma unroll
            for (int i = 0; i < 44; i++) kv[i] = 0.f;
            zz[0] = zz[1] = zz[2] = zz[3] = 0.f;
            fence_f(kv); fence_f(zz);
            const int vs = mi == 0 ? 0 : (mi == 1 ? 56 : 72);
            const uint64_t da = mkdesc(stg + mi * 1024, 5120, 128, 0);
            const uint64_t db = mkdesc(stg + 2560 + (vs >> 3) * 128, 5120, 128, 0);
            const uint64_t d1 = mkdesc(sb + K1_ONES, 0, 128, 0);
            WG_FENCE();
            #pragma unroll
            for (int k = 0; k < 8; k++) {
                wg_ss_n88_atbt(kv, da + k * 640, db + k * 640, 1);
                wg_ss_n8_atbt(zz, da + k * 640, d1, 1);
            }
            WG_COMMIT();
            WG_WAIT(0);
            fence_f(kv); fence_f(zz);
            #pragma unroll
            for (int r = 0; r < 2; r++) {
                const int pc = mi * 64 + w4 * 16 + g + 8 * r;
                if (pc < 160) {
                    const int e0 = vs + 2 * t - (pc / 20) * 20;
                    #pragma unroll
                    for (int j = 0; j < 11; j++) {
                        const int e = e0 + 8 * j;
                        if (e >= 0 && e < 20) *(float2*)(kvo + pc * 24 + e) = make_float2(kv[4*j + 2*r], kv[4*j + 2*r + 1]);
                    }
                    if (t == 0) kvo[3840 + pc] = zz[2 * r];
                }
            }
            FENCE_ASYNC();
            __syncwarp();
            if (lane == 0) mbar_arrive(K1_BAR(18));
            if (tid == 256) {
                mbar_wait(K1_BAR(18), 0);
                bulk_store(g_kvpart + (size_t)(mt * NH + hg * 8) * 480, stg + 81920, 15360);
                bulk_store(g_zpart + (mt * NH + hg * 8) * 20, stg + 97280, 640);
                asm volatile("cp.async.bulk.commit_group;" ::: "memory");
            }
            __syncwarp();
        }
        do_gate = wg == 0;
    }
    if (do_gate) {
        const int nr = br ? 2 : 4;
        #pragma unroll 1
        for (int r0 = 0; r0 < nr; r0 += 2) {
            const int row = mt * 128 + grp * 16 + (warp & 7) * nr + r0;
            float s0 = 0.f, s1 = 0.f;
            uint4 v0[3], v1[3], w[3];
            #pragma unroll
            for (int c = 0; c < 3; c++) {
                const int ch = min(lane + 32 * c, 79);
                v0[c] = *(const uint4*)(x + row * DM + ch * 8); v1[c] = *(const uint4*)(x + (row + 1) * DM + ch * 8); w[c] = *(const uint4*)(gate_w + ch * 8);
            }
            if (lane >= 16) w[2] = make_uint4(0, 0, 0, 0);
            #pragma unroll
            for (int c = 0; c < 3; c++) {
                s0 += dot_bf(v0[c].x, w[c].x) + dot_bf(v0[c].y, w[c].y) + dot_bf(v0[c].z, w[c].z) + dot_bf(v0[c].w, w[c].w);
                s1 += dot_bf(v1[c].x, w[c].x) + dot_bf(v1[c].y, w[c].y) + dot_bf(v1[c].z, w[c].z) + dot_bf(v1[c].w, w[c].w);
            }
            #pragma unroll
            for (int o = 16; o; o >>= 1) { s0 += __shfl_xor_sync(0xffffffffu, s0, o); s1 += __shfl_xor_sync(0xffffffffu, s1, o); }
            if (lane < 2) g_gate[row + lane] = bfr(1.f / (1.f + __expf(-bfr(lane ? s1 : s0))));
        }
    }
    if (warp == 8) asm volatile("cp.async.bulk.wait_group.read 0;" ::: "memory");
    TS_MAX(3); CK(0, 5);
}

#define K2_SMEM (196608 + 12288 + 1024)
#define PQN_LATE 0
#define LOOPV 0
struct PolyC { uint32_t one, cm15, c3, c2, c1, c0; };
__device__ __forceinline__ uint32_t hfma2bf(uint32_t a, uint32_t b, uint32_t c) { uint32_t r; asm("fma.rn.bf16x2 %0, %1, %2, %3;" : "=r"(r) : "r"(a), "r"(b), "r"(c)); return r; }
__device__ __forceinline__ uint32_t hadd2bf(uint32_t a, uint32_t b) { uint32_t r; asm("add.rn.bf16x2 %0, %1, %2;" : "=r"(r) : "r"(a), "r"(b)); return r; }
__device__ __forceinline__ uint32_t exp2_poly2(float y0, float y1, const PolyC& pc) {
    const uint32_t sch = __byte_perm(__float_as_uint(y0), __float_as_uint(y1), 0x6521);
    uint32_t m; asm("lop3.b32 %0, %1, 0x007F007F, %2, 0xEA;" : "=r"(m) : "r"(sch), "r"(pc.one));
    return hfma2bf(hfma2bf(m, pc.c2, pc.c1), m, pc.c0) + sch;
    const uint32_t d = hadd2bf(m, pc.cm15);
    uint32_t r = hfma2bf(d, pc.c2, pc.c1);
    r = hfma2bf(r, d, pc.c0);
    return r + sch;
}
template<int PAR>
__device__ __forceinline__ void softmax_blk(const float (&s)[32], uint32_t (&p)[16], const PolyC& pc) {
    #pragma unroll
    for (int j = 0; j < 8; j++) {
        if ((POLY_MASK >> (PAR * 8 + j)) & 1) {
            p[2*j] = exp2_poly2(s[4*j], s[4*j+1], pc);
            p[2*j+1] = exp2_poly2(s[4*j+2], s[4*j+3], pc);
        } else {
            p[2*j] = packbf(ex2f(s[4*j]), ex2f(s[4*j+1]));
            p[2*j+1] = packbf(ex2f(s[4*j+2]), ex2f(s[4*j+3]));
        }
    }
}

template<int HALF>
__device__ __forceinline__ void softmax_half(const float (&s)[64], uint32_t (&p)[16], const PolyC& pc) {
    #pragma unroll
    for (int j = 0; j < 8; j++) {
        const int b = 32 * HALF + 4 * j;
        if ((POLY_MASK >> (HALF * 8 + j)) & 1) {
            p[2*j] = exp2_poly2(s[b], s[b+1], pc);
            p[2*j+1] = exp2_poly2(s[b+2], s[b+3], pc);
        } else {
            p[2*j] = packbf(ex2f(s[b]), ex2f(s[b+1]));
            p[2*j+1] = packbf(ex2f(s[b+2]), ex2f(s[b+3]));
        }
    }
}

__device__ __noinline__ void aux_work(uint8_t* smem, int ax, const __nv_bfloat16* __restrict__ a_wo) {
    float* kvs = (float*)smem;
    const int tid = threadIdx.x;
    for (int i = tid; i < 3840; i += 512) {
        float s = 0.f;
        #pragma unroll
        for (int m = 0; m < 16; m++) s += g_kvpart[(size_t)(m * NH + ax * 8) * 480 + i];
        kvs[i] = s;
    }
    __syncthreads();
    #pragma unroll 1
    for (int it = tid; it < 8 * 5 * 80; it += 512) {
        const int cc = it % 80, dq = (it / 80) % 5, h = it / 400;
        float a[4][8];
        #pragma unroll
        for (int r = 0; r < 4; r++)
            #pragma unroll
            for (int i = 0; i < 8; i++) a[r][i] = 0.f;
        const __nv_bfloat16* wp = a_wo + (size_t)((ax * 8 + h) * DH) * DM + cc * 8;
        const float* kp = kvs + (h * 20 + dq * 4) * 24;
        #pragma unroll 5
        for (int e = 0; e < 20; e++) {
            const uint4 w = *(const uint4*)(wp + e * DM);
            const float wf[8] = {bflo(w.x), bfhi(w.x), bflo(w.y), bfhi(w.y), bflo(w.z), bfhi(w.z), bflo(w.w), bfhi(w.w)};
            #pragma unroll
            for (int r = 0; r < 4; r++) {
                const float k = kp[r * 24 + e];
                #pragma unroll
                for (int i = 0; i < 8; i++) a[r][i] += k * wf[i];
            }
        }
        #pragma unroll
        for (int r = 0; r < 4; r++)
            *(uint4*)(g_wm + (size_t)((ax * 8 + h) * DH + dq * 4 + r) * DM + cc * 8) =
                make_uint4(packbf(a[r][0], a[r][1]), packbf(a[r][2], a[r][3]), packbf(a[r][4], a[r][5]), packbf(a[r][6], a[r][7]));
    }
}

__global__ void __launch_bounds__(512, 1)
attn_kernel(const __nv_bfloat16* __restrict__ a_wo) {
    extern __shared__ __align__(1024) uint8_t smem[];
    const uint32_t sb = smem_u32(smem);
    const uint32_t bars = sb + 196608 + 12288;
    const int tid = threadIdx.x, warp = tid >> 5, lane = tid & 31;
    GRIDDEP_LAUNCH();
    if (blockIdx.x < 4) {
        GRIDDEP_WAIT();
        aux_work(smem, blockIdx.x, a_wo);
        TS_MAX(13);
        return;
    }
    const int h = (blockIdx.x - 4) >> 2, qb = blockIdx.x & 3;
    if (tid == 0) {
        for (int i = 0; i < 17; i++) mbar_init(bars + 8 * i, 1);
        asm volatile("fence.mbarrier_init.release.cluster;" ::: "memory");
        mbar_arrive(bars + 128);
    }
    TS_MIN(4);
    GRIDDEP_WAIT();
    TS_MIN(5); TS_MAX(17); CK(1, 0);
    const int wg = warp >> 2, w4 = warp & 3, g = lane >> 2, t = lane & 3;
    const uint8_t* kvsrc = g_kvimg + (size_t)h * 196608;
    if (tid == 0) {
        for (int i = 0; i < 2; i++) { mbar_expect(bars + 8 * i, 12288); bulk_load(sb + i * 12288, kvsrc + i * 12288, 12288, bars + 8 * i); }
    }
    const int rbase = qb * 512 + wg * 128 + w4 * 16 + g;
    const int fb = (5 * h) >> 1;
    const bool odd = h & 1;
    const bool cslot = odd ? t < 2 : t >= 2;
    const uint32_t qo = ((rbase >> 3) * 80 + fb) * 128 + lane * 4;
    uint32_t qv[2][3];
    float kmax, gt[4] = {0.f, 0.f, 0.f, 0.f};
    {
        #pragma unroll
        for (int r = 0; r < 2; r++) {
            qv[r][0] = *(const uint32_t*)(g_qb + qo + r * 10240); qv[r][1] = *(const uint32_t*)(g_qb + qo + r * 10240 + 128); qv[r][2] = *(const uint32_t*)(g_qb + qo + r * 10240 + 256);
        }
        const float4 kn4 = *(const float4*)(g_kn2 + h * 128 + lane * 4);
        float kn = fmaxf(fmaxf(kn4.x, kn4.y), fmaxf(kn4.z, kn4.w));
        #pragma unroll
        for (int o = 16; o; o >>= 1) kn = fmaxf(kn, __shfl_xor_sync(0xffffffffu, kn, o));
        kmax = sqrtf(kn);
        CK(1, 3);
        __syncthreads();
        CK(1, 4);
        if (tid == 0) {
            for (int i = 2; i < 16; i++) { mbar_expect(bars + 8 * i, 12288); bulk_load(sb + i * 12288, kvsrc + i * 12288, 12288, bars + 8 * i); }
        }
        __syncwarp();
    }
    PolyC pc;
    asm volatile("mov.b32 %0, 0x3F803F80;" : "=r"(pc.one));
    asm volatile("mov.b32 %0, 0xBFC0BFC0;" : "=r"(pc.cm15));
    pc.c3 = 0;
    asm volatile("mov.b32 %0, 0x42304230;" : "=r"(pc.c2));
    asm volatile("mov.b32 %0, 0xBF7CBF7C;" : "=r"(pc.c1));
    asm volatile("mov.b32 %0, 0x43744375;" : "=r"(pc.c0));
    pc.c2 = 0x42274229u + blockIdx.y;
    pc.one = 0x3F803F80u + blockIdx.y;
    asm volatile("mov.b32 %0, 0xC2FDC300;" : "=r"(pc.c1));
    asm volatile("mov.b32 %0, 0x43AA43AB;" : "=r"(pc.c0));

    #pragma unroll 1
    for (int tile = 0; tile < 2; tile++) {
        const int row0 = rbase + tile * 64;
        uint32_t q[8];
        if (cslot) { if (odd) { qv[0][0] = 0u; qv[1][0] = 0u; } else { qv[0][2] = 0u; qv[1][2] = 0u; } }
        q[0] = qv[0][0]; q[1] = qv[1][0]; q[2] = qv[0][1]; q[3] = qv[1][1]; q[4] = qv[0][2]; q[5] = qv[1][2];
        q[6] = blockIdx.y; q[7] = blockIdx.y;
        float n0 = bflo(q[0]) * bflo(q[0]) + bfhi(q[0]) * bfhi(q[0]) + bflo(q[2]) * bflo(q[2]) + bfhi(q[2]) * bfhi(q[2]) + bflo(q[4]) * bflo(q[4]) + bfhi(q[4]) * bfhi(q[4]);
        float n1 = bflo(q[1]) * bflo(q[1]) + bfhi(q[1]) * bfhi(q[1]) + bflo(q[3]) * bflo(q[3]) + bfhi(q[3]) * bfhi(q[3]) + bflo(q[5]) * bflo(q[5]) + bfhi(q[5]) * bfhi(q[5]);
        n0 += __shfl_xor_sync(0xffffffffu, n0, 1); n1 += __shfl_xor_sync(0xffffffffu, n1, 1);
        n0 += __shfl_xor_sync(0xffffffffu, n0, 2); n1 += __shfl_xor_sync(0xffffffffu, n1, 2);
        const float m0 = sqrtf(n0) * kmax * 1.02f + 0.0625f, m1 = sqrtf(n1) * kmax * 1.02f + 0.0625f;
        uint32_t unsafe = !(m0 <= 48.f && m1 <= 48.f);
        asm volatile("{.reg .pred p, q; setp.ne.u32 p, %0, 0; barrier.red.or.pred q, %1, 128, p; selp.u32 %0, 1, 0, q;}" : "+r"(unsafe) : "r"(wg + 1) : "memory");
        unsafe = __any_sync(0xffffffffu, unsafe);

        CK(1, 8 + tile * 3);
        float o[12];
        #pragma unroll
        for (int i = 0; i < 12; i++) o[i] = 0.f;
        fence_f(o);
        const uint64_t dk = mkdesc(sb, 128, 768, 0), dk2 = mkdesc(sb + 256, 0, 768, 0), dv = mkdesc(sb + 384, 768, 128, 0);
        float S[32];
        uint32_t p[16];
        if (!unsafe) {
            if (cslot) {
                const uint32_t c0 = (t & 1) ? 0x3B80u : ((packbf(-m0, 0.f) & 0xFFFFu) | 0x43FC0000u);
                const uint32_t c1 = (t & 1) ? 0x3B80u : ((packbf(-m1, 0.f) & 0xFFFFu) | 0x43FC0000u);
                if (odd) { q[0] = c0; q[1] = c1; } else { q[4] = c0; q[5] = c1; }
            }
            uint64_t ck = dk, ck2 = dk2, cv = dv;
            uint32_t cb = bars;
            mbar_wait(cb, 0);
            WG_FENCE();
            wg_qk0(S, q[0], q[1], q[2], q[3], ck); wg_qk1(S, q[4], q[5], q[6], q[7], ck2);
            WG_COMMIT();
            WG_WAIT(0);
            fence_f(S);
            #pragma unroll 1
            for (int c = 0; c < 16; c++) {
                softmax_blk<0>(S, p, pc);
                fence_r(p);
                WG_FENCE();
                wg_qk0(S, q[0], q[1], q[2], q[3], ck + 384); wg_qk1(S, q[4], q[5], q[6], q[7], ck2 + 384);
                #pragma unroll
                for (int k = 0; k < 4; k++) wg_pv(o, p[4*k], p[4*k+1], p[4*k+2], p[4*k+3], cv + k * 96);
                WG_COMMIT();
                WG_WAIT(0);
                fence_f(S);
                softmax_blk<1>(S, p, pc);
                fence_r(p);
                cb += 8; ck += 768; ck2 += 768;
                mbar_wait(cb, 0);
                WG_FENCE();
                wg_qk0(S, q[0], q[1], q[2], q[3], ck); wg_qk1(S, q[4], q[5], q[6], q[7], ck2);
                #pragma unroll
                for (int k = 0; k < 4; k++) wg_pv(o, p[4*k], p[4*k+1], p[4*k+2], p[4*k+3], cv + 384 + k * 96);
                WG_COMMIT();
                cv += 768;
                WG_WAIT(0);
                fence_f(S);
            }
        } else {
            float rm0 = -INFINITY, rm1 = -INFINITY;
            #pragma unroll 1
            for (int b = 0; b < 32; b++) {
                if ((b & 1) == 0) mbar_wait(bars + 8 * (b >> 1), 0);
                WG_FENCE();
                wg_qk0(S, q[0], q[1], q[2], q[3], dk + b * 384); wg_qk1(S, q[4], q[5], q[6], q[7], dk2 + b * 384);
                WG_COMMIT();
                WG_WAIT(0);
                fence_f(S);
                float x0 = rm0, x1 = rm1;
                #pragma unroll
                for (int j = 0; j < 8; j++) { x0 = fmaxf(x0, fmaxf(S[4*j], S[4*j+1])); x1 = fmaxf(x1, fmaxf(S[4*j+2], S[4*j+3])); }
                x0 = fmaxf(x0, __shfl_xor_sync(0xffffffffu, x0, 1)); x1 = fmaxf(x1, __shfl_xor_sync(0xffffffffu, x1, 1));
                x0 = fmaxf(x0, __shfl_xor_sync(0xffffffffu, x0, 2)); x1 = fmaxf(x1, __shfl_xor_sync(0xffffffffu, x1, 2));
                const float c0 = ex2f(rm0 - x0), c1 = ex2f(rm1 - x1);
                rm0 = x0; rm1 = x1;
                #pragma unroll
                for (int j = 0; j < 3; j++) { o[4*j] *= c0; o[4*j+1] *= c0; o[4*j+2] *= c1; o[4*j+3] *= c1; }
                #pragma unroll
                for (int j = 0; j < 8; j++) {
                    p[2*j] = packbf(ex2f(S[4*j] - x0), ex2f(S[4*j+1] - x0));
                    p[2*j+1] = packbf(ex2f(S[4*j+2] - x1), ex2f(S[4*j+3] - x1));
                }
                fence_r(p); fence_f(o);
                WG_FENCE();
                #pragma unroll
                for (int k = 0; k < 4; k++) wg_pv(o, p[4*k], p[4*k+1], p[4*k+2], p[4*k+3], dv + b * 384 + k * 96);
                WG_COMMIT();
                WG_WAIT(0);
                fence_f(o);
            }
        }
        fence_f(o);
        CK(1, 9 + tile * 3);
        const int src = (lane & ~3) | (odd ? 0 : 2);
        const float l0 = __shfl_sync(0xffffffffu, odd ? o[0] : o[8], src), l1 = __shfl_sync(0xffffffffu, odd ? o[2] : o[10], src);
        if (tile == 0) {
            uint32_t pv[4][3];
            float zs = 0.f;
            #pragma unroll
            for (int r = 0; r < 4; r++) {
                const uint32_t po = qo + ((r & 1) + (r >> 1) * 8) * 10240;
                pv[r][0] = *(const uint32_t*)(g_pq + po); pv[r][1] = *(const uint32_t*)(g_pq + po + 128); pv[r][2] = *(const uint32_t*)(g_pq + po + 256);
                gt[r] = g_gate[rbase + (r & 1) * 8 + (r >> 1) * 64];
            }
            #pragma unroll
            for (int r = 0; r < 2; r++) {
                qv[r][0] = *(const uint32_t*)(g_qb + qo + 81920 + r * 10240); qv[r][1] = *(const uint32_t*)(g_qb + qo + 81920 + r * 10240 + 128);
                qv[r][2] = *(const uint32_t*)(g_qb + qo + 81920 + r * 10240 + 256);
            }
            const int d = lane - (odd ? 4 : 0);
            if (d >= 0 && d < 20) {
                #pragma unroll
                for (int m = 0; m < 16; m++) zs += g_zpart[(m * NH + h) * 20 + d];
            }
            float z[6];
            #pragma unroll
            for (int j = 0; j < 3; j++) { z[2*j] = __shfl_sync(0xffffffffu, zs, 8 * j + 2 * t); z[2*j+1] = __shfl_sync(0xffffffffu, zs, 8 * j + 2 * t + 1); }
            #pragma unroll
            for (int r = 0; r < 4; r++) {
                float den = bflo(pv[r][0]) * z[0] + bfhi(pv[r][0]) * z[1] + bflo(pv[r][1]) * z[2] + bfhi(pv[r][1]) * z[3] + bflo(pv[r][2]) * z[4] + bfhi(pv[r][2]) * z[5];
                den += __shfl_xor_sync(0xffffffffu, den, 1);
                den += __shfl_xor_sync(0xffffffffu, den, 2);
                const float sc = gt[r] / (den + 1e-6f);
                const int tg = (rbase >> 3) + (r & 1) + (r >> 1) * 8;
                #pragma unroll
                for (int j = 0; j < 3; j++) {
                    const int kb = fb + j;
                    if (!(cslot && j == (odd ? 0 : 2)))
                        *(uint32_t*)(g_acat + (((kb >> 3) * 256 + tg) * 8 + (kb & 7)) * 128 + lane * 4) = packbf(bflo(pv[r][j]) * sc, bfhi(pv[r][j]) * sc);
                }
            }
        } else { gt[0] = gt[2]; gt[1] = gt[3]; }
        const float s0 = bfr(1.f - gt[0]) / l0, s1 = bfr(1.f - gt[1]) / l1;
        #pragma unroll
        for (int j = 0; j < 3; j++) {
            const int kb = 80 + fb + j;
            uint8_t* dst = g_acat + (((kb >> 3) * 256 + (row0 >> 3)) * 8 + (kb & 7)) * 128 + lane * 4;
            if (!(cslot && j == (odd ? 0 : 2))) {
                *(uint32_t*)dst = packbf(o[4*j] * s0, o[4*j+1] * s0);
                *(uint32_t*)(dst + 1024) = packbf(o[4*j+2] * s1, o[4*j+3] * s1);
            }
        }
    }
    TS_MAX(7);
}

__constant__ uint8_t k3_map[130] = {0,1,2,3,16,17,18,19,32,33,34,35,48,49,50,51,4,5,6,7,20,21,22,23,36,37,38,39,52,53,54,55,8,9,24,25,40,41,56,57,64,65,66,67,80,81,82,83,96,97,98,99,112,113,114,115,68,69,70,71,84,85,86,87,100,101,102,103,116,117,118,119,72,73,88,89,104,105,120,121,128,129,130,131,144,145,146,147,160,161,162,163,176,177,178,179,132,133,134,135,148,149,150,151,164,165,166,167,180,181,182,183,136,137,152,153,168,169,184,185,192,193,194,195,196,197,198,199,200,201};
#define K3_STAGE 28672
#define K3_NST 7
#define K3_SMEM (K3_NST * K3_STAGE + 1024)
__global__ void __launch_bounds__(160, 1)
out_kernel(const __grid_constant__ CUtensorMap tm_wm, const __grid_constant__ CUtensorMap tm_wob,
           __nv_bfloat16* __restrict__ out) {
    extern __shared__ __align__(1024) uint8_t smem[];
    const uint32_t sb = smem_u32(smem);
    const uint32_t bar_full = sb + K3_NST * K3_STAGE, bar_empty = bar_full + 64;
    const int tid = threadIdx.x, warp = tid >> 5, lane = tid & 31;
    const int tt = k3_map[blockIdx.x] >> 4, ct = k3_map[blockIdx.x] & 15;
    if (tid == 0) {
        for (int i = 0; i < K3_NST; i++) { mbar_init(bar_full + 8 * i, 1); mbar_init(bar_empty + 8 * i, 4); }
        asm volatile("fence.mbarrier_init.release.cluster;" ::: "memory");
    }
    __syncthreads();
    CK3(0);
    if (warp == 4) {
        if (lane == 0) {
            for (int it = 0; it < K3_NST; it++) {
                mbar_expect(bar_full + 8 * it, K3_STAGE);
                tma2d(sb + it * K3_STAGE, &tm_wob, bar_full + 8 * it, ct * 64, it * 64);
            }
            TS_MIN(8);
            GRIDDEP_WAIT();
            TS_MIN(9); TS_MAX(18); CK3(1);
            for (int it = 0; it < 20; it++) {
                const int s = it % K3_NST;
                const uint32_t st = sb + s * K3_STAGE, fb = bar_full + 8 * s;
                if (it >= K3_NST) {
                    mbar_wait(bar_empty + 8 * s, ((it / K3_NST) - 1) & 1);
                    mbar_expect(fb, K3_STAGE);
                    tma2d(st, it < 10 ? &tm_wob : &tm_wm, fb, ct * 64, (it % 10) * 64);
                }
                bulk_load(st + 8192, g_acat + (size_t)(((it + 10) % 20) * 256 + tt * 20) * 1024, 20480, fb);
            }
        }
    } else {
        float acc[80];
        #pragma unroll
        for (int i = 0; i < 80; i++) acc[i] = 0.f;
        fence_f(acc);
        for (int it = 0; it < 20; it++) {
            const int s = it % K3_NST;
            mbar_wait(bar_full + 8 * s, (it / K3_NST) & 1);
            if (it == 0) CK3(2); if (it == 6) CK3(3); if (it == 12) CK3(4);
            const uint32_t st = sb + s * K3_STAGE;
            const uint64_t da = mkdesc(st, 8192, 1024, 1), db = mkdesc(st + 8192, 128, 1024, 0);
            WG_FENCE();
            #pragma unroll
            for (int k = 0; k < 4; k++) wg_ss_n160_at(acc, da + k * 128, db + k * 16, 1);
            WG_COMMIT();
            WG_WAIT(1);
            if (it > 0 && lane == 0) mbar_arrive(bar_empty + 8 * ((it - 1) % K3_NST));
        }
        WG_WAIT(0);
        fence_f(acc);
        CK3(5);
        named_bar(1, 128);
        #pragma unroll
        for (int j = 0; j < 20; j += 2) {
            const int tok = 8 * (j + (lane >> 4)) + (lane & 7);
            const int chunk = (2 * warp + ((lane >> 3) & 1)) ^ (tok & 7);
            const uint32_t addr = sb + tok * 128 + chunk * 16;
            asm volatile("stmatrix.sync.aligned.m8n8.x4.trans.shared.b16 [%0], {%1,%2,%3,%4};" :: "r"(addr),
                "r"(packbf(acc[4*j], acc[4*j+1])), "r"(packbf(acc[4*j+2], acc[4*j+3])), "r"(packbf(acc[4*j+4], acc[4*j+5])), "r"(packbf(acc[4*j+6], acc[4*j+7])) : "memory");
        }
        named_bar(1, 128);
        #pragma unroll
        for (int i = 0; i < 10; i++) {
            const int idx = tid + 128 * i, tok = idx >> 3, ch = idx & 7;
            const int gtok = tt * 160 + tok;
            const uint4 v = *(const uint4*)(smem + tok * 128 + ((ch ^ (tok & 7)) * 16));
            if (gtok < SEQ) *(uint4*)(out + (size_t)gtok * DM + ct * 64 + ch * 8) = v;
        }
        TS_MAX(10); CK3(6);
    }
}

typedef CUresult (*PFN_tmapEncode)(CUtensorMap*, CUtensorMapDataType, cuuint32_t, void*, const cuuint64_t*, const cuuint64_t*, const cuuint32_t*, const cuuint32_t*,
                                   CUtensorMapInterleave, CUtensorMapSwizzle, CUtensorMapL2promotion, CUtensorMapFloatOOBfill);
static void make_map(PFN_tmapEncode enc, CUtensorMap* tm, const void* ptr, uint64_t cols, uint64_t rows, uint32_t bcols, uint32_t brows) {
    cuuint64_t gd[2] = {cols, rows}; cuuint64_t gs[1] = {cols * 2}; cuuint32_t bx[2] = {bcols, brows}; cuuint32_t es[2] = {1, 1};
    enc(tm, CU_TENSOR_MAP_DATA_TYPE_BFLOAT16, 2, (void*)ptr, gd, gs, bx, es, CU_TENSOR_MAP_INTERLEAVE_NONE, CU_TENSOR_MAP_SWIZZLE_128B,
        CU_TENSOR_MAP_L2_PROMOTION_L2_128B, CU_TENSOR_MAP_FLOAT_OOB_FILL_NONE);
}

extern "C" void kernel_launch(void* const* d_in, const int* in_sizes, int n_in, void* d_out, int out_size) {
    const __nv_bfloat16* x = (const __nv_bfloat16*)d_in[0];
    const __nv_bfloat16* a_wqkv = (const __nv_bfloat16*)d_in[1];
    const __nv_bfloat16* a_wo = (const __nv_bfloat16*)d_in[2];
    const __nv_bfloat16* b_wqkv = (const __nv_bfloat16*)d_in[4];
    const __nv_bfloat16* b_wo = (const __nv_bfloat16*)d_in[5];
    const __nv_bfloat16* gate_w = (const __nv_bfloat16*)d_in[6];
    static CUtensorMap tm_x, tm_wm, tm_wob;
    static WMaps tm_w;
    static const void* cached[4] = {nullptr, nullptr, nullptr, nullptr};
    if (cached[0] != x || cached[1] != a_wqkv || cached[2] != b_wqkv || cached[3] != b_wo) {
        void* fn = nullptr; cudaDriverEntryPointQueryResult qr;
        cudaGetDriverEntryPoint("cuTensorMapEncodeTiled", &fn, cudaEnableDefault, &qr);
        PFN_tmapEncode enc = (PFN_tmapEncode)fn;
        void* p_wm;
        cudaGetSymbolAddress(&p_wm, g_wm);
        make_map(enc, &tm_x, x, DM, SEQ, 64, 128);
        for (int i = 0; i < 4; i++) {
            cuuint64_t gd[4] = {64, DM, 10, 3}; cuuint64_t gs[3] = {3 * DM * 2, 128, DM * 2};
            cuuint32_t bx[4] = {64, 64, 3, (cuuint32_t)((i & 1) ? 1 : 2)}; cuuint32_t es[4] = {1, 1, 1, 1};
            enc(&tm_w.m[i], CU_TENSOR_MAP_DATA_TYPE_BFLOAT16, 4, (void*)(i < 2 ? a_wqkv : b_wqkv), gd, gs, bx, es, CU_TENSOR_MAP_INTERLEAVE_NONE,
                CU_TENSOR_MAP_SWIZZLE_128B, CU_TENSOR_MAP_L2_PROMOTION_L2_128B, CU_TENSOR_MAP_FLOAT_OOB_FILL_NONE);
        }
        make_map(enc, &tm_wm, p_wm, DM, DM, 64, 64);
        make_map(enc, &tm_wob, b_wo, DM, DM, 64, 64);
        cudaFuncSetAttribute(qkv_kernel, cudaFuncAttributeMaxDynamicSharedMemorySize, K1_SMEM);
        cudaFuncSetAttribute(attn_kernel, cudaFuncAttributeMaxDynamicSharedMemorySize, K2_SMEM);
        cudaFuncSetAttribute(out_kernel, cudaFuncAttributeMaxDynamicSharedMemorySize, K3_SMEM);
        cached[0] = x; cached[1] = a_wqkv; cached[2] = b_wqkv; cached[3] = b_wo;
    }
    cudaStream_t st = cudaStreamPerThread;
    cudaLaunchAttribute at[1];
    at[0].id = cudaLaunchAttributeProgrammaticStreamSerialization; at[0].val.programmaticStreamSerializationAllowed = 1;
    cudaLaunchConfig_t cfg = {};
    cfg.stream = st;
    cfg.gridDim = dim3(128); cfg.blockDim = dim3(512); cfg.dynamicSmemBytes = K1_SMEM; cfg.attrs = at; cfg.numAttrs = 0;
    cudaLaunchKernelEx(&cfg, qkv_kernel, tm_x, tm_w, x, gate_w, a_wo, b_wo);
    cfg.gridDim = dim3(132); cfg.blockDim = dim3(512); cfg.dynamicSmemBytes = K2_SMEM; cfg.numAttrs = 1;
    cudaLaunchKernelEx(&cfg, attn_kernel, a_wo);
    cfg.gridDim = dim3(130); cfg.blockDim = dim3(160); cfg.dynamicSmemBytes = K3_SMEM; cfg.numAttrs = 1;
    cudaLaunchKernelEx(&cfg, out_kernel, tm_wm, tm_wob, (__nv_bfloat16*)d_out);
}
```

```cpp
#include <cuda_runtime.h>
#include <cuda_bf16.h>
#include <cuda.h>
#include <stdint.h>

#define SEQ 2048
#define DM 640
#define NH 32
#define DH 20

#define POLY_MASK 0xD5DDu

__device__ __align__(1024) uint8_t g_kvimg[NH * 196608];
__device__ __align__(1024) uint8_t g_qb[SEQ * DM * 2];
__device__ __align__(1024) uint8_t g_pq[SEQ * DM * 2];
__device__ __align__(1024) uint8_t g_acat[SEQ * 2 * DM * 2 + 4096];
__device__ __align__(1024) __nv_bfloat16 g_wm[DM * DM];
__device__ __align__(16) float g_kvpart[16 * NH * 480];
__device__ __align__(16) float g_zpart[16 * NH * 20];
__device__ __align__(16) float g_kn2[NH * 128];
__device__ __align__(16) float g_gate[SEQ];

__device__ __forceinline__ uint32_t smem_u32(const void* p) { return (uint32_t)__cvta_generic_to_shared(p); }
__device__ __forceinline__ uint64_t mkdesc(uint32_t saddr, uint32_t lbo, uint32_t sbo, uint32_t swz) {
    return (uint64_t)((saddr & 0x3FFFF) >> 4) | ((uint64_t)(lbo >> 4) << 16) | ((uint64_t)(sbo >> 4) << 32) | ((uint64_t)swz << 62);
}
#define WG_FENCE() asm volatile("wgmma.fence.sync.aligned;" ::: "memory")
#define WG_COMMIT() asm volatile("wgmma.commit_group.sync.aligned;" ::: "memory")
#define WG_WAIT(n) asm volatile("wgmma.wait_group.sync.aligned %0;" :: "n"(n) : "memory")
template<int N> __device__ __forceinline__ void fence_f(float (&d)[N]) {
    #pragma unroll
    for (int i = 0; i < N; i++) asm volatile("" : "+f"(d[i]) :: "memory");
}
template<int N> __device__ __forceinline__ void fence_r(uint32_t (&d)[N]) {
    #pragma unroll
    for (int i = 0; i < N; i++) asm volatile("" : "+r"(d[i]) :: "memory");
}
__device__ __forceinline__ void mbar_init(uint32_t bar, uint32_t cnt) { asm volatile("mbarrier.init.shared::cta.b64 [%0], %1;" :: "r"(bar), "r"(cnt)); }
__device__ __forceinline__ void mbar_expect(uint32_t bar, uint32_t bytes) { asm volatile("mbarrier.arrive.expect_tx.shared::cta.b64 _, [%0], %1;" :: "r"(bar), "r"(bytes) : "memory"); }
__device__ __forceinline__ void mbar_arrive(uint32_t bar) { asm volatile("mbarrier.arrive.shared::cta.b64 _, [%0];" :: "r"(bar) : "memory"); }
__device__ __forceinline__ void mbar_wait(uint32_t bar, uint32_t parity) {
    asm volatile("{\n.reg .pred p;\nWAIT_%=:\nmbarrier.try_wait.parity.shared::cta.b64 p, [%0], %1;\n@p bra DONE_%=;\nbra WAIT_%=;\nDONE_%=:\n}" :: "r"(bar), "r"(parity) : "memory");
}
__device__ __forceinline__ void tma2d(uint32_t dst, const CUtensorMap* tm, uint32_t bar, int c0, int c1) {
    asm volatile("cp.async.bulk.tensor.2d.shared::cluster.global.mbarrier::complete_tx::bytes [%0], [%1, {%3,%4}], [%2];"
        :: "r"(dst), "l"((uint64_t)tm), "r"(bar), "r"(c0), "r"(c1) : "memory");
}
__device__ __forceinline__ void bulk_load(uint32_t dst, const void* src, uint32_t bytes, uint32_t bar) {
    asm volatile("cp.async.bulk.shared::cluster.global.mbarrier::complete_tx::bytes [%0], [%1], %2, [%3];" :: "r"(dst), "l"(src), "r"(bytes), "r"(bar) : "memory");
}
__device__ __forceinline__ void named_bar(int id, int n) { asm volatile("bar.sync %0, %1;" :: "r"(id), "r"(n) : "memory"); }
__device__ __forceinline__ float ex2f(float x) { float y; asm("ex2.approx.ftz.f32 %0, %1;" : "=f"(y) : "f"(x)); return y; }
__device__ __forceinline__ uint32_t packbf(float lo, float hi) { uint32_t r; asm("cvt.rn.bf16x2.f32 %0, %1, %2;" : "=r"(r) : "f"(hi), "f"(lo)); return r; }
__device__ __forceinline__ float bflo(uint32_t v) { return __uint_as_float(v << 16); }
__device__ __forceinline__ float bfhi(uint32_t v) { return __uint_as_float(v & 0xFFFF0000u); }
__device__ __forceinline__ float bfr(float v) { return bflo(packbf(v, 0.f)); }
__device__ __forceinline__ float dot_bf(uint32_t a, uint32_t b) {
    uint32_t p; asm("mul.rn.bf16x2 %0, %1, %2;" : "=r"(p) : "r"(a), "r"(b));
    return bflo(p) + bfhi(p);
}
__device__ __forceinline__ float phi_f(float t) { return (fmaxf(t, 0.f) + 1e-6f) + ex2f(fminf(t, 0.f) * 1.4426950408889634f); }
#define GRIDDEP_WAIT() asm volatile("griddepcontrol.wait;" ::: "memory")
#define GRIDDEP_LAUNCH() asm volatile("griddepcontrol.launch_dependents;" ::: "memory")

#define TS_MIN(i)
#define CK(k, i)
#define CK3(i)
#define TS_MAX(i)

__device__ __forceinline__ void wg_rs_n128_bt(float (&d)[64], uint32_t a0, uint32_t a1, uint32_t a2, uint32_t a3, uint64_t db) {
    asm volatile("wgmma.mma_async.sync.aligned.m64n128k16.f32.bf16.bf16 {%0,%1,%2,%3,%4,%5,%6,%7,%8,%9,%10,%11,%12,%13,%14,%15,%16,%17,%18,%19,%20,%21,%22,%23,%24,%25,%26,%27,%28,%29,%30,%31,%32,%33,%34,%35,%36,%37,%38,%39,%40,%41,%42,%43,%44,%45,%46,%47,%48,%49,%50,%51,%52,%53,%54,%55,%56,%57,%58,%59,%60,%61,%62,%63}, {%64,%65,%66,%67}, %68, 1, 1, 1, 1;"
      : "+f"(d[0]),"+f"(d[1]),"+f"(d[2]),"+f"(d[3]),"+f"(d[4]),"+f"(d[5]),"+f"(d[6]),"+f"(d[7]),"+f"(d[8]),"+f"(d[9]),"+f"(d[10]),"+f"(d[11]),"+f"(d[12]),"+f"(d[13]),"+f"(d[14]),"+f"(d[15]),"+f"(d[16]),"+f"(d[17]),"+f"(d[18]),"+f"(d[19]),"+f"(d[20]),"+f"(d[21]),"+f"(d[22]),"+f"(d[23]),"+f"(d[24]),"+f"(d[25]),"+f"(d[26]),"+f"(d[27]),"+f"(d[28]),"+f"(d[29]),"+f"(d[30]),"+f"(d[31]),"+f"(d[32]),"+f"(d[33]),"+f"(d[34]),"+f"(d[35]),"+f"(d[36]),"+f"(d[37]),"+f"(d[38]),"+f"(d[39]),"+f"(d[40]),"+f"(d[41]),"+f"(d[42]),"+f"(d[43]),"+f"(d[44]),"+f"(d[45]),"+f"(d[46]),"+f"(d[47]),"+f"(d[48]),"+f"(d[49]),"+f"(d[50]),"+f"(d[51]),"+f"(d[52]),"+f"(d[53]),"+f"(d[54]),"+f"(d[55]),"+f"(d[56]),"+f"(d[57]),"+f"(d[58]),"+f"(d[59]),"+f"(d[60]),"+f"(d[61]),"+f"(d[62]),"+f"(d[63]) : "r"(a0), "r"(a1), "r"(a2), "r"(a3), "l"(db));
}
__device__ __forceinline__ void wg_ss_n64_bt(float (&d)[32], uint64_t da, uint64_t db, int acc) {
    asm volatile("{.reg .pred p; setp.ne.b32 p, %34, 0;\n"
      "wgmma.mma_async.sync.aligned.m64n64k16.f32.bf16.bf16 {%0,%1,%2,%3,%4,%5,%6,%7,%8,%9,%10,%11,%12,%13,%14,%15,%16,%17,%18,%19,%20,%21,%22,%23,%24,%25,%26,%27,%28,%29,%30,%31}, %32, %33, p, 1, 1, 0, 1;}"
      : "+f"(d[0]),"+f"(d[1]),"+f"(d[2]),"+f"(d[3]),"+f"(d[4]),"+f"(d[5]),"+f"(d[6]),"+f"(d[7]),"+f"(d[8]),"+f"(d[9]),"+f"(d[10]),"+f"(d[11]),"+f"(d[12]),"+f"(d[13]),"+f"(d[14]),"+f"(d[15]),"+f"(d[16]),"+f"(d[17]),"+f"(d[18]),"+f"(d[19]),"+f"(d[20]),"+f"(d[21]),"+f"(d[22]),"+f"(d[23]),"+f"(d[24]),"+f"(d[25]),"+f"(d[26]),"+f"(d[27]),"+f"(d[28]),"+f"(d[29]),"+f"(d[30]),"+f"(d[31]) : "l"(da), "l"(db), "r"(acc));
}
__device__ __forceinline__ void wg_ss_n32_bt(float (&d)[16], uint64_t da, uint64_t db, int acc) {
    asm volatile("{.reg .pred p; setp.ne.b32 p, %18, 0;\n"
      "wgmma.mma_async.sync.aligned.m64n32k16.f32.bf16.bf16 {%0,%1,%2,%3,%4,%5,%6,%7,%8,%9,%10,%11,%12,%13,%14,%15}, %16, %17, p, 1, 1, 0, 1;}"
      : "+f"(d[0]),"+f"(d[1]),"+f"(d[2]),"+f"(d[3]),"+f"(d[4]),"+f"(d[5]),"+f"(d[6]),"+f"(d[7]),"+f"(d[8]),"+f"(d[9]),"+f"(d[10]),"+f"(d[11]),"+f"(d[12]),"+f"(d[13]),"+f"(d[14]),"+f"(d[15]) : "l"(da), "l"(db), "r"(acc));
}
__device__ __forceinline__ void wg_rs_n32_bt(float (&d)[16], uint32_t a0, uint32_t a1, uint32_t a2, uint32_t a3, uint64_t db) {
    asm volatile("wgmma.mma_async.sync.aligned.m64n32k16.f32.bf16.bf16 {%0,%1,%2,%3,%4,%5,%6,%7,%8,%9,%10,%11,%12,%13,%14,%15}, {%16,%17,%18,%19}, %20, 1, 1, 1, 1;"
      : "+f"(d[0]),"+f"(d[1]),"+f"(d[2]),"+f"(d[3]),"+f"(d[4]),"+f"(d[5]),"+f"(d[6]),"+f"(d[7]),"+f"(d[8]),"+f"(d[9]),"+f"(d[10]),"+f"(d[11]),"+f"(d[12]),"+f"(d[13]),"+f"(d[14]),"+f"(d[15]) : "r"(a0), "r"(a1), "r"(a2), "r"(a3), "l"(db));
}
__device__ __forceinline__ void wg_ss_n88_atbt(float (&d)[44], uint64_t da, uint64_t db, int acc) {
    asm volatile("{.reg .pred p; setp.ne.b32 p, %46, 0;\n"
      "wgmma.mma_async.sync.aligned.m64n88k16.f32.bf16.bf16 {%0,%1,%2,%3,%4,%5,%6,%7,%8,%9,%10,%11,%12,%13,%14,%15,%16,%17,%18,%19,%20,%21,%22,%23,%24,%25,%26,%27,%28,%29,%30,%31,%32,%33,%34,%35,%36,%37,%38,%39,%40,%41,%42,%43}, %44, %45, p, 1, 1, 1, 1;}"
      : "+f"(d[0]),"+f"(d[1]),"+f"(d[2]),"+f"(d[3]),"+f"(d[4]),"+f"(d[5]),"+f"(d[6]),"+f"(d[7]),"+f"(d[8]),"+f"(d[9]),"+f"(d[10]),"+f"(d[11]),"+f"(d[12]),"+f"(d[13]),"+f"(d[14]),"+f"(d[15]),"+f"(d[16]),"+f"(d[17]),"+f"(d[18]),"+f"(d[19]),"+f"(d[20]),"+f"(d[21]),"+f"(d[22]),"+f"(d[23]),"+f"(d[24]),"+f"(d[25]),"+f"(d[26]),"+f"(d[27]),"+f"(d[28]),"+f"(d[29]),"+f"(d[30]),"+f"(d[31]),"+f"(d[32]),"+f"(d[33]),"+f"(d[34]),"+f"(d[35]),"+f"(d[36]),"+f"(d[37]),"+f"(d[38]),"+f"(d[39]),"+f"(d[40]),"+f"(d[41]),"+f"(d[42]),"+f"(d[43]) : "l"(da), "l"(db), "r"(acc));
}
__device__ __forceinline__ void wg_ss_n8_atbt(float (&d)[4], uint64_t da, uint64_t db, int acc) {
    asm volatile("{.reg .pred p; setp.ne.b32 p, %6, 0;\n"
      "wgmma.mma_async.sync.aligned.m64n8k16.f32.bf16.bf16 {%0,%1,%2,%3}, %4, %5, p, 1, 1, 1, 1;}"
      : "+f"(d[0]),"+f"(d[1]),"+f"(d[2]),"+f"(d[3]) : "l"(da), "l"(db), "r"(acc));
}
__device__ __forceinline__ void wg_ss_n160_at(float (&d)[80], uint64_t da, uint64_t db, int acc) {
    asm volatile("{.reg .pred p; setp.ne.b32 p, %82, 0;\n"
      "wgmma.mma_async.sync.aligned.m64n160k16.f32.bf16.bf16 {%0,%1,%2,%3,%4,%5,%6,%7,%8,%9,%10,%11,%12,%13,%14,%15,%16,%17,%18,%19,%20,%21,%22,%23,%24,%25,%26,%27,%28,%29,%30,%31,%32,%33,%34,%35,%36,%37,%38,%39,%40,%41,%42,%43,%44,%45,%46,%47,%48,%49,%50,%51,%52,%53,%54,%55,%56,%57,%58,%59,%60,%61,%62,%63,%64,%65,%66,%67,%68,%69,%70,%71,%72,%73,%74,%75,%76,%77,%78,%79}, %80, %81, p, 1, 1, 1, 0;}"
      : "+f"(d[0]),"+f"(d[1]),"+f"(d[2]),"+f"(d[3]),"+f"(d[4]),"+f"(d[5]),"+f"(d[6]),"+f"(d[7]),"+f"(d[8]),"+f"(d[9]),"+f"(d[10]),"+f"(d[11]),"+f"(d[12]),"+f"(d[13]),"+f"(d[14]),"+f"(d[15]),"+f"(d[16]),"+f"(d[17]),"+f"(d[18]),"+f"(d[19]),"+f"(d[20]),"+f"(d[21]),"+f"(d[22]),"+f"(d[23]),"+f"(d[24]),"+f"(d[25]),"+f"(d[26]),"+f"(d[27]),"+f"(d[28]),"+f"(d[29]),"+f"(d[30]),"+f"(d[31]),"+f"(d[32]),"+f"(d[33]),"+f"(d[34]),"+f"(d[35]),"+f"(d[36]),"+f"(d[37]),"+f"(d[38]),"+f"(d[39]),"+f"(d[40]),"+f"(d[41]),"+f"(d[42]),"+f"(d[43]),"+f"(d[44]),"+f"(d[45]),"+f"(d[46]),"+f"(d[47]),"+f"(d[48]),"+f"(d[49]),"+f"(d[50]),"+f"(d[51]),"+f"(d[52]),"+f"(d[53]),"+f"(d[54]),"+f"(d[55]),"+f"(d[56]),"+f"(d[57]),"+f"(d[58]),"+f"(d[59]),"+f"(d[60]),"+f"(d[61]),"+f"(d[62]),"+f"(d[63]),"+f"(d[64]),"+f"(d[65]),"+f"(d[66]),"+f"(d[67]),"+f"(d[68]),"+f"(d[69]),"+f"(d[70]),"+f"(d[71]),"+f"(d[72]),"+f"(d[73]),"+f"(d[74]),"+f"(d[75]),"+f"(d[76]),"+f"(d[77]),"+f"(d[78]),"+f"(d[79]) : "l"(da), "l"(db), "r"(acc));
}
__device__ __forceinline__ void wg_qk0(float (&d)[32], uint32_t a0, uint32_t a1, uint32_t a2, uint32_t a3, uint64_t db) {
    asm volatile("wgmma.mma_async.sync.aligned.m64n64k16.f32.bf16.bf16 {%0,%1,%2,%3,%4,%5,%6,%7,%8,%9,%10,%11,%12,%13,%14,%15,%16,%17,%18,%19,%20,%21,%22,%23,%24,%25,%26,%27,%28,%29,%30,%31}, {%32,%33,%34,%35}, %36, 0, 1, 1, 0;"
      : "+f"(d[0]),"+f"(d[1]),"+f"(d[2]),"+f"(d[3]),"+f"(d[4]),"+f"(d[5]),"+f"(d[6]),"+f"(d[7]),"+f"(d[8]),"+f"(d[9]),"+f"(d[10]),"+f"(d[11]),"+f"(d[12]),"+f"(d[13]),"+f"(d[14]),"+f"(d[15]),"+f"(d[16]),"+f"(d[17]),"+f"(d[18]),"+f"(d[19]),"+f"(d[20]),"+f"(d[21]),"+f"(d[22]),"+f"(d[23]),"+f"(d[24]),"+f"(d[25]),"+f"(d[26]),"+f"(d[27]),"+f"(d[28]),"+f"(d[29]),"+f"(d[30]),"+f"(d[31]) : "r"(a0), "r"(a1), "r"(a2), "r"(a3), "l"(db));
}
__device__ __forceinline__ void wg_qk1(float (&d)[32], uint32_t a0, uint32_t a1, uint32_t a2, uint32_t a3, uint64_t db) {
    asm volatile("wgmma.mma_async.sync.aligned.m64n64k16.f32.bf16.bf16 {%0,%1,%2,%3,%4,%5,%6,%7,%8,%9,%10,%11,%12,%13,%14,%15,%16,%17,%18,%19,%20,%21,%22,%23,%24,%25,%26,%27,%28,%29,%30,%31}, {%32,%33,%34,%35}, %36, 1, 1, 1, 0;"
      : "+f"(d[0]),"+f"(d[1]),"+f"(d[2]),"+f"(d[3]),"+f"(d[4]),"+f"(d[5]),"+f"(d[6]),"+f"(d[7]),"+f"(d[8]),"+f"(d[9]),"+f"(d[10]),"+f"(d[11]),"+f"(d[12]),"+f"(d[13]),"+f"(d[14]),"+f"(d[15]),"+f"(d[16]),"+f"(d[17]),"+f"(d[18]),"+f"(d[19]),"+f"(d[20]),"+f"(d[21]),"+f"(d[22]),"+f"(d[23]),"+f"(d[24]),"+f"(d[25]),"+f"(d[26]),"+f"(d[27]),"+f"(d[28]),"+f"(d[29]),"+f"(d[30]),"+f"(d[31]) : "r"(a0), "r"(a1), "r"(a2), "r"(a3), "l"(db));
}
__device__ __forceinline__ void wg_pv(float (&d)[12], uint32_t a0, uint32_t a1, uint32_t a2, uint32_t a3, uint64_t db) {
    asm volatile("wgmma.mma_async.sync.aligned.m64n24k16.f32.bf16.bf16 {%0,%1,%2,%3,%4,%5,%6,%7,%8,%9,%10,%11}, {%12,%13,%14,%15}, %16, 1, 1, 1, 1;"
      : "+f"(d[0]),"+f"(d[1]),"+f"(d[2]),"+f"(d[3]),"+f"(d[4]),"+f"(d[5]),"+f"(d[6]),"+f"(d[7]),"+f"(d[8]),"+f"(d[9]),"+f"(d[10]),"+f"(d[11]) : "r"(a0), "r"(a1), "r"(a2), "r"(a3), "l"(db));
}

#define K1_ONES 204800
#define K1_BARS 205056
#define K1_SMEM 205312
#define QSCALE 0.32259799f
#define K1_BAR(i) (sb + K1_BARS + 8 * (i))

__device__ __forceinline__ void tma4d(uint32_t dst, const CUtensorMap* tm, uint32_t bar, int c0, int c1, int c2, int c3) {
    asm volatile("cp.async.bulk.tensor.4d.shared::cluster.global.mbarrier::complete_tx::bytes [%0], [%1, {%3,%4,%5,%6}], [%2];"
        :: "r"(dst), "l"((uint64_t)tm), "r"(bar), "r"(c0), "r"(c1), "r"(c2), "r"(c3) : "memory");
}
__device__ __forceinline__ void k1_issue(int pass, int kb, uint32_t sb, const CUtensorMap* tx, const CUtensorMap* tw, int mt, int hg) {
    const int s = pass ? kb % 5 : kb % 3;
    const uint32_t st = sb + (pass ? s * 40960 : s * 65536), fb = K1_BAR(pass ? s : 10 + s);
    mbar_expect(fb, pass ? 40960 : 65536);
    tma2d(st, tx, fb, kb * 64, mt * 128);
    tma4d(st + 16384, tw + pass, fb, 0, kb * 64, (hg * 160) >> 6, 1 - pass);
}
__device__ __forceinline__ void stsm4(uint32_t addr, uint32_t r0, uint32_t r1, uint32_t r2, uint32_t r3) {
    asm volatile("stmatrix.sync.aligned.m8n8.x4.shared.b16 [%0], {%1,%2,%3,%4};" :: "r"(addr), "r"(r0), "r"(r1), "r"(r2), "r"(r3) : "memory");
}
__device__ __forceinline__ void bulk_store(void* dst, uint32_t src, uint32_t bytes) {
    asm volatile("cp.async.bulk.global.shared::cta.bulk_group [%0], [%1], %2;" :: "l"(dst), "r"(src), "r"(bytes) : "memory");
}
#define FENCE_ASYNC() asm volatile("fence.proxy.async.shared::cta;" ::: "memory")

__device__ __forceinline__ void k1_stage_rows(const uint32_t (&pk)[40], uint32_t base, bool odd) {
    const uint32_t b0 = base + (odd ? 512 : 0), b2 = base + (odd ? 0 : 2048);
    #pragma unroll
    for (int j = 0; j < 16; j += 2) stsm4(b0 + j * 128, pk[2*j], pk[2*j+1], pk[2*j+2], pk[2*j+3]);
    #pragma unroll
    for (int j = 0; j < 4; j += 2) stsm4(b2 + j * 128, pk[32 + 2*j], pk[33 + 2*j], pk[34 + 2*j], pk[35 + 2*j]);
}
template<bool ODD>
__device__ __forceinline__ void k1_image(const uint32_t (&pk)[40], uint32_t base, int lane) {
    #define PH(j) (ODD ? ((j) < 4 ? (j) + 16 : (j) - 4) : (j))
    const bool hi = lane & 16;
    #pragma unroll
    for (int i = 0; i < 4; i++) {
        const uint32_t e = base + (2 * i) * 12288, o = e + 12288;
        const int j = 5 * i;
        stsm4(hi ? e + 128 : e, pk[2*PH(j)], pk[2*PH(j)+1], pk[2*PH(j+1)], pk[2*PH(j+1)+1]);
        stsm4(hi ? o : e + 256, pk[2*PH(j+2)], pk[2*PH(j+2)+1], pk[2*PH(j+2)], pk[2*PH(j+2)+1]);
        stsm4(hi ? o + 256 : o + 128, pk[2*PH(j+3)], pk[2*PH(j+3)+1], pk[2*PH(j+4)], pk[2*PH(j+4)+1]);
    }
}
template<bool ODD>
__device__ __forceinline__ void k1_norms(const uint32_t (&pk)[40], int lane, float* kn_dst) {
    {
        const bool lo = (lane & 3) < 2;
        #pragma unroll
        for (int h = 0; h < 8; h++) {
            float a = 0.f, b = 0.f;
            #pragma unroll
            for (int jj = 0; jj < 3; jj++) {
                const int j = (5 * h) / 2 + jj;
                const uint32_t v0 = pk[2*PH(j)], v1 = pk[2*PH(j)+1];
                float s0 = bflo(v0) * bflo(v0) + bfhi(v0) * bfhi(v0), s1 = bflo(v1) * bflo(v1) + bfhi(v1) * bfhi(v1);
                if (jj == ((h & 1) ? 0 : 2)) { const bool mine = (h & 1) ? !lo : lo; s0 = mine ? s0 : 0.f; s1 = mine ? s1 : 0.f; }
                a += s0; b += s1;
            }
            a += __shfl_xor_sync(0xffffffffu, a, 1); b += __shfl_xor_sync(0xffffffffu, b, 1);
            a += __shfl_xor_sync(0xffffffffu, a, 2); b += __shfl_xor_sync(0xffffffffu, b, 2);
            a = fmaxf(a, b);
            a = fmaxf(a, __shfl_xor_sync(0xffffffffu, a, 4));
            a = fmaxf(a, __shfl_xor_sync(0xffffffffu, a, 8));
            a = fmaxf(a, __shfl_xor_sync(0xffffffffu, a, 16));
            if (lane == h) kn_dst[h * 128] = a;
        }
    }
    #undef PH
}

struct WMaps { CUtensorMap m[4]; };
__global__ void __launch_bounds__(512, 1)
qkv_kernel(const __grid_constant__ CUtensorMap tm_x, const __grid_constant__ WMaps tm_w,
           const __nv_bfloat16* __restrict__ x, const __nv_bfloat16* __restrict__ gate_w) {
    extern __shared__ __align__(1024) uint8_t smem[];
    const uint32_t sb = smem_u32(smem);
    const int tid = threadIdx.x, warp = tid >> 5, lane = tid & 31;
    const int mt = ((blockIdx.x >> 4) & 3) * 4 + (blockIdx.x & 3), grp = (blockIdx.x >> 6) * 4 + ((blockIdx.x >> 2) & 3), br = grp >> 2, hg = grp & 3;
    const CUtensorMap* tw = &tm_w.m[br * 2];
    TS_MIN(0); CK(0, 0);
    if (tid == 0) {
        for (int i = 0; i < 5; i++) { mbar_init(K1_BAR(i), 1); mbar_init(K1_BAR(5 + i), 16); }
        for (int i = 0; i < 3; i++) { mbar_init(K1_BAR(10 + i), 1); mbar_init(K1_BAR(13 + i), 16); }
        mbar_init(K1_BAR(16), 16); mbar_init(K1_BAR(17), 16); mbar_init(K1_BAR(18), 12);
        asm volatile("fence.mbarrier_init.release.cluster;" ::: "memory");
        k1_issue(1, 0, sb, &tm_x, tw, mt, hg);
    }
    __syncthreads();
    GRIDDEP_LAUNCH();
    if (tid == 0) for (int i = 1; i < 5; i++) k1_issue(1, i, sb, &tm_x, tw, mt, hg);
    if (tid >= 64 && tid < 96) *(uint32_t*)(smem + K1_ONES + lane * 4) = (lane & 3) == 0 ? 0x3F80u : 0u;
    __syncwarp();
    const int wg = __shfl_sync(0xffffffffu, warp >> 2, 0), mh = wg & 1, sel = wg >> 1, w4 = warp & 3;
    const int g = lane >> 2, t = lane & 3;
    const bool odd = hg & 1;
    CK(0, 1);
    {
        float a0[32], a2[16];
        #pragma unroll
        for (int i = 0; i < 32; i++) a0[i] = 0.f;
        #pragma unroll
        for (int i = 0; i < 16; i++) a2[i] = 0.f;
        fence_f(a0); fence_f(a2);
        const uint32_t o0 = sel ? 512 : (odd ? 1024 : 0), o2 = odd ? 4 : 1024;
        for (int kb = 0; kb < 10; kb++) {
            const int s = kb % 5;
            mbar_wait(K1_BAR(s), kb >= 5);
            const uint32_t st = sb + s * 40960;
            const uint64_t da = mkdesc(st + mh * 8192, 16, 1024, 1), db = mkdesc(st + 16384, 8192, 1024, 1);
            WG_FENCE();
            #pragma unroll
            for (int k = 0; k < 4; k++) wg_ss_n64_bt(a0, da + k * 2, db + o0 + k * 128, 1);
            if (sel) {
                #pragma unroll
                for (int k = 0; k < 4; k++) wg_ss_n32_bt(a2, da + k * 2, db + o2 + k * 128, 1);
            }
            WG_COMMIT();
            WG_WAIT(0);
            if (lane == 0) mbar_arrive(K1_BAR(5 + s));
            if (tid == 0) {
                mbar_wait(K1_BAR(5 + s), kb >= 5);
                if (kb < 5) k1_issue(1, kb + 5, sb, &tm_x, tw, mt, hg);
                else if (kb == 6) k1_issue(0, 0, sb, &tm_x, tw, mt, hg);
                else if (kb >= 8) k1_issue(0, kb - 7, sb, &tm_x, tw, mt, hg);
            }
            __syncwarp();
        }
        fence_f(a0); fence_f(a2);
        CK(0, 2);
        uint8_t* dst = (br ? g_qb : g_pq) + ((mt * 16 + mh * 8 + w4 * 2) * 80 + hg * 20) * 128 + lane * 4;
        uint8_t* d0 = dst + (sel ? (odd ? 4 : 8) : (odd ? 12 : 0)) * 128;
        uint8_t* d2 = dst + (odd ? 0 : 16) * 128;
        if (br) {
            #pragma unroll
            for (int j = 0; j < 8; j++) {
                *(uint32_t*)(d0 + j * 128) = packbf(a0[4*j] * QSCALE, a0[4*j+1] * QSCALE);
                *(uint32_t*)(d0 + 10240 + j * 128) = packbf(a0[4*j+2] * QSCALE, a0[4*j+3] * QSCALE);
            }
            if (sel) {
                #pragma unroll
                for (int j = 0; j < 4; j++) {
                    *(uint32_t*)(d2 + j * 128) = packbf(a2[4*j] * QSCALE, a2[4*j+1] * QSCALE);
                    *(uint32_t*)(d2 + 10240 + j * 128) = packbf(a2[4*j+2] * QSCALE, a2[4*j+3] * QSCALE);
                }
            }
        } else {
            #pragma unroll
            for (int j = 0; j < 8; j++) {
                *(uint32_t*)(d0 + j * 128) = packbf(phi_f(a0[4*j]), phi_f(a0[4*j+1]));
                *(uint32_t*)(d0 + 10240 + j * 128) = packbf(phi_f(a0[4*j+2]), phi_f(a0[4*j+3]));
            }
            if (sel) {
                #pragma unroll
                for (int j = 0; j < 4; j++) {
                    *(uint32_t*)(d2 + j * 128) = packbf(phi_f(a2[4*j]), phi_f(a2[4*j+1]));
                    *(uint32_t*)(d2 + 10240 + j * 128) = packbf(phi_f(a2[4*j+2]), phi_f(a2[4*j+3]));
                }
            }
        }
    }
    CK(0, 3);
    uint32_t pk[40];
    {
        float a0[64], a2[16];
        #pragma unroll
        for (int i = 0; i < 64; i++) a0[i] = 0.f;
        #pragma unroll
        for (int i = 0; i < 16; i++) a2[i] = 0.f;
        fence_f(a0); fence_f(a2);
        const uint32_t o0 = odd ? 512 : 0, o2 = odd ? 4 : 1024;
        const uint32_t arow = (mh * 64 + w4 * 16 + (lane & 15)) * 128;
        for (int kb = 0; kb < 10; kb++) {
            const int s = kb % 3;
            mbar_wait(K1_BAR(10 + s), (kb / 3) & 1);
            const uint32_t st = sb + s * 65536;
            const uint64_t db = mkdesc(st + 16384 + sel * 24576, 8192, 1024, 1);
            uint32_t af[4][4];
            #pragma unroll
            for (int k = 0; k < 4; k++)
                asm volatile("ldmatrix.sync.aligned.m8n8.x4.shared.b16 {%0,%1,%2,%3}, [%4];"
                    : "=r"(af[k][0]), "=r"(af[k][1]), "=r"(af[k][2]), "=r"(af[k][3]) : "r"(st + arow + (((2 * k + (lane >> 4)) ^ (lane & 7)) << 4)));
            WG_FENCE();
            #pragma unroll
            for (int k = 0; k < 4; k++) {
                wg_rs_n128_bt(a0, af[k][0], af[k][1], af[k][2], af[k][3], db + o0 + k * 128);
                wg_rs_n32_bt(a2, af[k][0], af[k][1], af[k][2], af[k][3], db + o2 + k * 128);
            }
            WG_COMMIT();
            WG_WAIT(0);
            const uint32_t eb = K1_BAR(kb == 9 ? 16 : 13 + s);
            if (lane == 0) mbar_arrive(eb);
            if (tid == 0 && kb < 7) { mbar_wait(eb, (kb / 3) & 1); k1_issue(0, kb + 3, sb, &tm_x, tw, mt, hg); }
            __syncwarp();
        }
        fence_f(a0); fence_f(a2);
        CK(0, 4);
        if (br == 0 && sel == 0) {
            #pragma unroll
            for (int i = 0; i < 32; i++) pk[i] = packbf(phi_f(a0[2 * i]), phi_f(a0[2 * i + 1]));
            #pragma unroll
            for (int i = 0; i < 8; i++) pk[32 + i] = packbf(phi_f(a2[2 * i]), phi_f(a2[2 * i + 1]));
        } else {
            #pragma unroll
            for (int i = 0; i < 32; i++) pk[i] = packbf(a0[2 * i], a0[2 * i + 1]);
            #pragma unroll
            for (int i = 0; i < 8; i++) pk[32 + i] = packbf(a2[2 * i], a2[2 * i + 1]);
        }
    }
    const int rg = mh * 8 + w4 * 2 + ((lane >> 3) & 1);
    mbar_wait(K1_BAR(14), 0); mbar_wait(K1_BAR(15), 0);
    const uint32_t stg = sb + 65536;
    bool do_gate;
    if (br) {
        const uint32_t base = stg + rg * 768 + sel * 384 + (lane & 7) * 16;
        if (odd) k1_image<true>(pk, base, lane); else k1_image<false>(pk, base, lane);
        __syncwarp();
        {
            const int lr = mh * 64 + w4 * 16 + (lane & 15);
            const uint32_t flag = (sel == 0 && ((POLY_MASK >> ((lr >> 3) & 15)) & 1)) ? 0x3F80u : 0u;
            const uint2 cv = make_uint2(0x3F80u | (flag << 16), flag);
            uint8_t* p = smem + 65536 + (lane >> 4) * 49152 + (lr >> 3) * 768 + sel * 384 + (lr & 7) * 16;
            *(uint2*)(p + 264) = cv; *(uint2*)(p + 12288) = cv; *(uint2*)(p + 24576 + 264) = cv; *(uint2*)(p + 36864) = cv;
        }
        FENCE_ASYNC();
        __syncwarp();
        if (lane == 0) mbar_arrive(K1_BAR(17));
        if (warp == 8 && lane < 8) {
            mbar_wait(K1_BAR(17), 0);
            bulk_store(g_kvimg + (size_t)(hg * 8 + lane) * 196608 + mt * 12288, stg + lane * 12288, 12288);
            asm volatile("cp.async.bulk.commit_group;" ::: "memory");
        }
        __syncwarp();
        if (sel == 0) {
            float* kd = g_kn2 + (hg * 8) * 128 + mt * 8 + mh * 4 + w4;
            if (odd) k1_norms<true>(pk, lane, kd); else k1_norms<false>(pk, lane, kd);
        }
        do_gate = sel == 1;
    } else {
        k1_stage_rows(pk, stg + rg * 5120 + sel * 2560 + (lane >> 4) * 128 + (lane & 7) * 16, odd);
        FENCE_ASYNC();
        __syncwarp();
        if (lane == 0) mbar_arrive(K1_BAR(17));
        if (wg != 0) {
            const int mi = wg - 1;
            mbar_wait(K1_BAR(17), 0);
            float* kvo = (float*)(smem + 65536 + 81920);
            float kv[44], zz[4];
            #pragma unroll
            for (int i = 0; i < 44; i++) kv[i] = 0.f;
            zz[0] = zz[1] = zz[2] = zz[3] = 0.f;
            fence_f(kv); fence_f(zz);
            const int vs = mi == 0 ? 0 : (mi == 1 ? 56 : 72);
            const uint64_t da = mkdesc(stg + mi * 1024, 5120, 128, 0);
            const uint64_t db = mkdesc(stg + 2560 + (vs >> 3) * 128, 5120, 128, 0);
            const uint64_t d1 = mkdesc(sb + K1_ONES, 0, 128, 0);
            WG_FENCE();
            #pragma unroll
            for (int k = 0; k < 8; k++) {
                wg_ss_n88_atbt(kv, da + k * 640, db + k * 640, 1);
                wg_ss_n8_atbt(zz, da + k * 640, d1, 1);
            }
            WG_COMMIT();
            WG_WAIT(0);
            fence_f(kv); fence_f(zz);
            #pragma unroll
            for (int r = 0; r < 2; r++) {
                const int pc = mi * 64 + w4 * 16 + g + 8 * r;
                if (pc < 160) {
                    const int e0 = vs + 2 * t - (pc / 20) * 20;
                    #pragma unroll
                    for (int j = 0; j < 11; j++) {
                        const int e = e0 + 8 * j;
                        if (e >= 0 && e < 20) *(float2*)(kvo + pc * 24 + e) = make_float2(kv[4*j + 2*r], kv[4*j + 2*r + 1]);
                    }
                    if (t == 0) kvo[3840 + pc] = zz[2 * r];
                }
            }
            FENCE_ASYNC();
            __syncwarp();
            if (lane == 0) mbar_arrive(K1_BAR(18));
            if (tid == 256) {
                mbar_wait(K1_BAR(18), 0);
                bulk_store(g_kvpart + (size_t)(mt * NH + hg * 8) * 480, stg + 81920, 15360);
                bulk_store(g_zpart + (mt * NH + hg * 8) * 20, stg + 97280, 640);
                asm volatile("cp.async.bulk.commit_group;" ::: "memory");
            }
            __syncwarp();
        }
        do_gate = wg == 0;
    }
    if (do_gate) {
        const int nr = br ? 2 : 4;
        #pragma unroll 1
        for (int r0 = 0; r0 < nr; r0 += 2) {
            const int row = mt * 128 + grp * 16 + (warp & 7) * nr + r0;
            float s0 = 0.f, s1 = 0.f;
            uint4 v0[3], v1[3], w[3];
            #pragma unroll
            for (int c = 0; c < 3; c++) {
                const int ch = min(lane + 32 * c, 79);
                v0[c] = *(const uint4*)(x + row * DM + ch * 8); v1[c] = *(const uint4*)(x + (row + 1) * DM + ch * 8); w[c] = *(const uint4*)(gate_w + ch * 8);
            }
            if (lane >= 16) w[2] = make_uint4(0, 0, 0, 0);
            #pragma unroll
            for (int c = 0; c < 3; c++) {
                s0 += dot_bf(v0[c].x, w[c].x) + dot_bf(v0[c].y, w[c].y) + dot_bf(v0[c].z, w[c].z) + dot_bf(v0[c].w, w[c].w);
                s1 += dot_bf(v1[c].x, w[c].x) + dot_bf(v1[c].y, w[c].y) + dot_bf(v1[c].z, w[c].z) + dot_bf(v1[c].w, w[c].w);
            }
            #pragma unroll
            for (int o = 16; o; o >>= 1) { s0 += __shfl_xor_sync(0xffffffffu, s0, o); s1 += __shfl_xor_sync(0xffffffffu, s1, o); }
            if (lane < 2) g_gate[row + lane] = bfr(1.f / (1.f + __expf(-bfr(lane ? s1 : s0))));
        }
    }
    if (warp == 8) asm volatile("cp.async.bulk.wait_group.read 0;" ::: "memory");
    TS_MAX(3); CK(0, 5);
}

#define K2_SMEM (196608 + 12288 + 1024)

struct PolyC { uint32_t one, c2; };
__device__ __forceinline__ uint32_t hfma2bf(uint32_t a, uint32_t b, uint32_t c) { uint32_t r; asm("fma.rn.bf16x2 %0, %1, %2, %3;" : "=r"(r) : "r"(a), "r"(b), "r"(c)); return r; }
__device__ __forceinline__ uint32_t exp2_poly2(float y0, float y1, const PolyC& pc) {
    const uint32_t sch = __byte_perm(__float_as_uint(y0), __float_as_uint(y1), 0x6521);
    uint32_t m; asm("lop3.b32 %0, %1, 0x007F007F, %2, 0xEA;" : "=r"(m) : "r"(sch), "r"(pc.one));
    return hfma2bf(hfma2bf(m, pc.c2, 0xC2FDC300u), m, 0x43AA43ABu) + sch;
}
template<int PAR>
__device__ __forceinline__ void softmax_blk(const float (&s)[32], uint32_t (&p)[16], const PolyC& pc) {
    #pragma unroll
    for (int j = 0; j < 8; j++) {
        if ((POLY_MASK >> (PAR * 8 + j)) & 1) {
            p[2*j] = exp2_poly2(s[4*j], s[4*j+1], pc);
            p[2*j+1] = exp2_poly2(s[4*j+2], s[4*j+3], pc);
        } else {
            p[2*j] = packbf(ex2f(s[4*j]), ex2f(s[4*j+1]));
            p[2*j+1] = packbf(ex2f(s[4*j+2]), ex2f(s[4*j+3]));
        }
    }
}

__device__ __noinline__ void aux_work(uint8_t* smem, int ax, const __nv_bfloat16* __restrict__ a_wo) {
    float* kvs = (float*)smem;
    const int tid = threadIdx.x;
    for (int i = tid; i < 3840; i += 512) {
        float s = 0.f;
        #pragma unroll
        for (int m = 0; m < 16; m++) s += g_kvpart[(size_t)(m * NH + ax * 8) * 480 + i];
        kvs[i] = s;
    }
    __syncthreads();
    #pragma unroll 1
    for (int it = tid; it < 8 * 5 * 80; it += 512) {
        const int cc = it % 80, dq = (it / 80) % 5, h = it / 400;
        float a[4][8];
        #pragma unroll
        for (int r = 0; r < 4; r++)
            #pragma unroll
            for (int i = 0; i < 8; i++) a[r][i] = 0.f;
        const __nv_bfloat16* wp = a_wo + (size_t)((ax * 8 + h) * DH) * DM + cc * 8;
        const float* kp = kvs + (h * 20 + dq * 4) * 24;
        #pragma unroll 5
        for (int e = 0; e < 20; e++) {
            const uint4 w = *(const uint4*)(wp + e * DM);
            const float wf[8] = {bflo(w.x), bfhi(w.x), bflo(w.y), bfhi(w.y), bflo(w.z), bfhi(w.z), bflo(w.w), bfhi(w.w)};
            #pragma unroll
            for (int r = 0; r < 4; r++) {
                const float k = kp[r * 24 + e];
                #pragma unroll
                for (int i = 0; i < 8; i++) a[r][i] += k * wf[i];
            }
        }
        #pragma unroll
        for (int r = 0; r < 4; r++)
            *(uint4*)(g_wm + (size_t)((ax * 8 + h) * DH + dq * 4 + r) * DM + cc * 8) =
                make_uint4(packbf(a[r][0], a[r][1]), packbf(a[r][2], a[r][3]), packbf(a[r][4], a[r][5]), packbf(a[r][6], a[r][7]));
    }
}

__global__ void __launch_bounds__(512, 1)
attn_kernel(const __nv_bfloat16* __restrict__ a_wo) {
    extern __shared__ __align__(1024) uint8_t smem[];
    const uint32_t sb = smem_u32(smem);
    const uint32_t bars = sb + 196608 + 12288;
    const int tid = threadIdx.x, warp = tid >> 5, lane = tid & 31;
    GRIDDEP_LAUNCH();
    if (blockIdx.x < 4) {
        GRIDDEP_WAIT();
        aux_work(smem, blockIdx.x, a_wo);
        TS_MAX(13);
        return;
    }
    const int h = (blockIdx.x - 4) >> 2, qb = blockIdx.x & 3;
    if (tid == 0) {
        for (int i = 0; i < 17; i++) mbar_init(bars + 8 * i, 1);
        asm volatile("fence.mbarrier_init.release.cluster;" ::: "memory");
        mbar_arrive(bars + 128);
    }
    TS_MIN(4);
    GRIDDEP_WAIT();
    TS_MIN(5); TS_MAX(17); CK(1, 0);
    const int wg = warp >> 2, w4 = warp & 3, g = lane >> 2, t = lane & 3;
    const uint8_t* kvsrc = g_kvimg + (size_t)h * 196608;
    if (tid == 0) {
        for (int i = 0; i < 2; i++) { mbar_expect(bars + 8 * i, 12288); bulk_load(sb + i * 12288, kvsrc + i * 12288, 12288, bars + 8 * i); }
    }
    const int rbase = qb * 512 + wg * 128 + w4 * 16 + g;
    const int fb = (5 * h) >> 1;
    const bool odd = h & 1;
    const bool cslot = odd ? t < 2 : t >= 2;
    const uint32_t qo = ((rbase >> 3) * 80 + fb) * 128 + lane * 4;
    uint32_t qv[2][3];
    float kmax, gt[4] = {0.f, 0.f, 0.f, 0.f};
    {
        #pragma unroll
        for (int r = 0; r < 2; r++) {
            qv[r][0] = *(const uint32_t*)(g_qb + qo + r * 10240); qv[r][1] = *(const uint32_t*)(g_qb + qo + r * 10240 + 128); qv[r][2] = *(const uint32_t*)(g_qb + qo + r * 10240 + 256);
        }
        const float4 kn4 = *(const float4*)(g_kn2 + h * 128 + lane * 4);
        float kn = fmaxf(fmaxf(kn4.x, kn4.y), fmaxf(kn4.z, kn4.w));
        #pragma unroll
        for (int o = 16; o; o >>= 1) kn = fmaxf(kn, __shfl_xor_sync(0xffffffffu, kn, o));
        kmax = sqrtf(kn);
        CK(1, 3);
        __syncthreads();
        CK(1, 4);
        if (tid == 0) {
            for (int i = 2; i < 16; i++) { mbar_expect(bars + 8 * i, 12288); bulk_load(sb + i * 12288, kvsrc + i * 12288, 12288, bars + 8 * i); }
        }
        __syncwarp();
    }
    PolyC pc;
    pc.c2 = 0x42274229u + blockIdx.y;
    pc.one = 0x3F803F80u + blockIdx.y;

    #pragma unroll 1
    for (int tile = 0; tile < 2; tile++) {
        const int row0 = rbase + tile * 64;
        uint32_t q[8];
        if (cslot) { if (odd) { qv[0][0] = 0u; qv[1][0] = 0u; } else { qv[0][2] = 0u; qv[1][2] = 0u; } }
        q[0] = qv[0][0]; q[1] = qv[1][0]; q[2] = qv[0][1]; q[3] = qv[1][1]; q[4] = qv[0][2]; q[5] = qv[1][2];
        q[6] = blockIdx.y; q[7] = blockIdx.y;
        float n0 = bflo(q[0]) * bflo(q[0]) + bfhi(q[0]) * bfhi(q[0]) + bflo(q[2]) * bflo(q[2]) + bfhi(q[2]) * bfhi(q[2]) + bflo(q[4]) * bflo(q[4]) + bfhi(q[4]) * bfhi(q[4]);
        float n1 = bflo(q[1]) * bflo(q[1]) + bfhi(q[1]) * bfhi(q[1]) + bflo(q[3]) * bflo(q[3]) + bfhi(q[3]) * bfhi(q[3]) + bflo(q[5]) * bflo(q[5]) + bfhi(q[5]) * bfhi(q[5]);
        n0 += __shfl_xor_sync(0xffffffffu, n0, 1); n1 += __shfl_xor_sync(0xffffffffu, n1, 1);
        n0 += __shfl_xor_sync(0xffffffffu, n0, 2); n1 += __shfl_xor_sync(0xffffffffu, n1, 2);
        const float m0 = sqrtf(n0) * kmax * 1.02f + 0.0625f, m1 = sqrtf(n1) * kmax * 1.02f + 0.0625f;
        uint32_t unsafe = !(m0 <= 48.f && m1 <= 48.f);
        asm volatile("{.reg .pred p, q; setp.ne.u32 p, %0, 0; barrier.red.or.pred q, %1, 128, p; selp.u32 %0, 1, 0, q;}" : "+r"(unsafe) : "r"(wg + 1) : "memory");
        unsafe = __any_sync(0xffffffffu, unsafe);

        CK(1, 8 + tile * 3);
        float o[12];
        #pragma unroll
        for (int i = 0; i < 12; i++) o[i] = 0.f;
        fence_f(o);
        const uint64_t dk = mkdesc(sb, 128, 768, 0), dk2 = mkdesc(sb + 256, 0, 768, 0), dv = mkdesc(sb + 384, 768, 128, 0);
        float S[32];
        uint32_t p[16];
        if (!unsafe) {
            if (cslot) {
                const uint32_t c0 = (t & 1) ? 0x3B80u : ((packbf(-m0, 0.f) & 0xFFFFu) | 0x43FC0000u);
                const uint32_t c1 = (t & 1) ? 0x3B80u : ((packbf(-m1, 0.f) & 0xFFFFu) | 0x43FC0000u);
                if (odd) { q[0] = c0; q[1] = c1; } else { q[4] = c0; q[5] = c1; }
            }
            uint64_t ck = dk, ck2 = dk2, cv = dv;
            uint32_t cb = bars;
            mbar_wait(cb, 0);
            WG_FENCE();
            wg_qk0(S, q[0], q[1], q[2], q[3], ck); wg_qk1(S, q[4], q[5], q[6], q[7], ck2);
            WG_COMMIT();
            WG_WAIT(0);
            fence_f(S);
            #pragma unroll 1
            for (int c = 0; c < 16; c++) {
                softmax_blk<0>(S, p, pc);
                fence_r(p);
                WG_FENCE();
                wg_qk0(S, q[0], q[1], q[2], q[3], ck + 384); wg_qk1(S, q[4], q[5], q[6], q[7], ck2 + 384);
                #pragma unroll
                for (int k = 0; k < 4; k++) wg_pv(o, p[4*k], p[4*k+1], p[4*k+2], p[4*k+3], cv + k * 96);
                WG_COMMIT();
                WG_WAIT(0);
                fence_f(S);
                softmax_blk<1>(S, p, pc);
                fence_r(p);
                cb += 8; ck += 768; ck2 += 768;
                mbar_wait(cb, 0);
                WG_FENCE();
                wg_qk0(S, q[0], q[1], q[2], q[3], ck); wg_qk1(S, q[4], q[5], q[6], q[7], ck2);
                #pragma unroll
                for (int k = 0; k < 4; k++) wg_pv(o, p[4*k], p[4*k+1], p[4*k+2], p[4*k+3], cv + 384 + k * 96);
                WG_COMMIT();
                cv += 768;
                WG_WAIT(0);
                fence_f(S);
            }
        } else {
            float rm0 = -INFINITY, rm1 = -INFINITY;
            #pragma unroll 1
            for (int b = 0; b < 32; b++) {
                if ((b & 1) == 0) mbar_wait(bars + 8 * (b >> 1), 0);
                WG_FENCE();
                wg_qk0(S, q[0], q[1], q[2], q[3], dk + b * 384); wg_qk1(S, q[4], q[5], q[6], q[7], dk2 + b * 384);
                WG_COMMIT();
                WG_WAIT(0);
                fence_f(S);
                float x0 = rm0, x1 = rm1;
                #pragma unroll
                for (int j = 0; j < 8; j++) { x0 = fmaxf(x0, fmaxf(S[4*j], S[4*j+1])); x1 = fmaxf(x1, fmaxf(S[4*j+2], S[4*j+3])); }
                x0 = fmaxf(x0, __shfl_xor_sync(0xffffffffu, x0, 1)); x1 = fmaxf(x1, __shfl_xor_sync(0xffffffffu, x1, 1));
                x0 = fmaxf(x0, __shfl_xor_sync(0xffffffffu, x0, 2)); x1 = fmaxf(x1, __shfl_xor_sync(0xffffffffu, x1, 2));
                const float c0 = ex2f(rm0 - x0), c1 = ex2f(rm1 - x1);
                rm0 = x0; rm1 = x1;
                #pragma unroll
                for (int j = 0; j < 3; j++) { o[4*j] *= c0; o[4*j+1] *= c0; o[4*j+2] *= c1; o[4*j+3] *= c1; }
                #pragma unroll
                for (int j = 0; j < 8; j++) {
                    p[2*j] = packbf(ex2f(S[4*j] - x0), ex2f(S[4*j+1] - x0));
                    p[2*j+1] = packbf(ex2f(S[4*j+2] - x1), ex2f(S[4*j+3] - x1));
                }
                fence_r(p); fence_f(o);
                WG_FENCE();
                #pragma unroll
                for (int k = 0; k < 4; k++) wg_pv(o, p[4*k], p[4*k+1], p[4*k+2], p[4*k+3], dv + b * 384 + k * 96);
                WG_COMMIT();
                WG_WAIT(0);
                fence_f(o);
            }
        }
        fence_f(o);
        CK(1, 9 + tile * 3);
        const int src = (lane & ~3) | (odd ? 0 : 2);
        const float l0 = __shfl_sync(0xffffffffu, odd ? o[0] : o[8], src), l1 = __shfl_sync(0xffffffffu, odd ? o[2] : o[10], src);
        if (tile == 0) {
            uint32_t pv[4][3];
            float zs = 0.f;
            #pragma unroll
            for (int r = 0; r < 4; r++) {
                const uint32_t po = qo + ((r & 1) + (r >> 1) * 8) * 10240;
                pv[r][0] = *(const uint32_t*)(g_pq + po); pv[r][1] = *(const uint32_t*)(g_pq + po + 128); pv[r][2] = *(const uint32_t*)(g_pq + po + 256);
                gt[r] = g_gate[rbase + (r & 1) * 8 + (r >> 1) * 64];
            }
            #pragma unroll
            for (int r = 0; r < 2; r++) {
                qv[r][0] = *(const uint32_t*)(g_qb + qo + 81920 + r * 10240); qv[r][1] = *(const uint32_t*)(g_qb + qo + 81920 + r * 10240 + 128);
                qv[r][2] = *(const uint32_t*)(g_qb + qo + 81920 + r * 10240 + 256);
            }
            const int d = lane - (odd ? 4 : 0);
            if (d >= 0 && d < 20) {
                #pragma unroll
                for (int m = 0; m < 16; m++) zs += g_zpart[(m * NH + h) * 20 + d];
            }
            float z[6];
            #pragma unroll
            for (int j = 0; j < 3; j++) { z[2*j] = __shfl_sync(0xffffffffu, zs, 8 * j + 2 * t); z[2*j+1] = __shfl_sync(0xffffffffu, zs, 8 * j + 2 * t + 1); }
            #pragma unroll
            for (int r = 0; r < 4; r++) {
                float den = bflo(pv[r][0]) * z[0] + bfhi(pv[r][0]) * z[1] + bflo(pv[r][1]) * z[2] + bfhi(pv[r][1]) * z[3] + bflo(pv[r][2]) * z[4] + bfhi(pv[r][2]) * z[5];
                den += __shfl_xor_sync(0xffffffffu, den, 1);
                den += __shfl_xor_sync(0xffffffffu, den, 2);
                const float sc = gt[r] / (den + 1e-6f);
                const int tg = (rbase >> 3) + (r & 1) + (r >> 1) * 8;
                #pragma unroll
                for (int j = 0; j < 3; j++) {
                    const int kb = fb + j;
                    if (!(cslot && j == (odd ? 0 : 2)))
                        *(uint32_t*)(g_acat + (((kb >> 3) * 256 + tg) * 8 + (kb & 7)) * 128 + lane * 4) = packbf(bflo(pv[r][j]) * sc, bfhi(pv[r][j]) * sc);
                }
            }
        } else { gt[0] = gt[2]; gt[1] = gt[3]; }
        const float s0 = bfr(1.f - gt[0]) / l0, s1 = bfr(1.f - gt[1]) / l1;
        #pragma unroll
        for (int j = 0; j < 3; j++) {
            const int kb = 80 + fb + j;
            uint8_t* dst = g_acat + (((kb >> 3) * 256 + (row0 >> 3)) * 8 + (kb & 7)) * 128 + lane * 4;
            if (!(cslot && j == (odd ? 0 : 2))) {
                *(uint32_t*)dst = packbf(o[4*j] * s0, o[4*j+1] * s0);
                *(uint32_t*)(dst + 1024) = packbf(o[4*j+2] * s1, o[4*j+3] * s1);
            }
        }
    }
    TS_MAX(7);
}

__constant__ uint8_t k3_map[130] = {0,1,2,3,16,17,18,19,32,33,34,35,48,49,50,51,4,5,6,7,20,21,22,23,36,37,38,39,52,53,54,55,8,9,24,25,40,41,56,57,64,65,66,67,80,81,82,83,96,97,98,99,112,113,114,115,68,69,70,71,84,85,86,87,100,101,102,103,116,117,118,119,72,73,88,89,104,105,120,121,128,129,130,131,144,145,146,147,160,161,162,163,176,177,178,179,132,133,134,135,148,149,150,151,164,165,166,167,180,181,182,183,136,137,152,153,168,169,184,185,192,193,194,195,196,197,198,199,200,201};
#define K3_STAGE 28672
#define K3_NST 6
#define K3_SMEM (K3_NST * K3_STAGE + 1024)
__global__ void __launch_bounds__(160, 1)
out_kernel(const __grid_constant__ CUtensorMap tm_wm, const __grid_constant__ CUtensorMap tm_wob,
           __nv_bfloat16* __restrict__ out) {
    extern __shared__ __align__(1024) uint8_t smem[];
    const uint32_t sb = smem_u32(smem);
    const uint32_t bar_full = sb + K3_NST * K3_STAGE, bar_empty = bar_full + 64;
    const int tid = threadIdx.x, warp = tid >> 5, lane = tid & 31;
    const int tt = k3_map[blockIdx.x] >> 4, ct = k3_map[blockIdx.x] & 15;
    if (tid == 0) {
        for (int i = 0; i < K3_NST; i++) { mbar_init(bar_full + 8 * i, 1); mbar_init(bar_empty + 8 * i, 4); }
        asm volatile("fence.mbarrier_init.release.cluster;" ::: "memory");
    }
    __syncthreads();
    CK3(0);
    if (warp == 4) {
        if (lane == 0) {
            for (int it = 0; it < K3_NST; it++) {
                mbar_expect(bar_full + 8 * it, K3_STAGE);
                tma2d(sb + it * K3_STAGE, &tm_wob, bar_full + 8 * it, ct * 64, it * 64);
            }
            TS_MIN(8);
            GRIDDEP_WAIT();
            TS_MIN(9); TS_MAX(18); CK3(1);
            for (int it = 0; it < 20; it++) {
                const int s = it % K3_NST;
                const uint32_t st = sb + s * K3_STAGE, fb = bar_full + 8 * s;
                if (it >= K3_NST) {
                    mbar_wait(bar_empty + 8 * s, ((it / K3_NST) - 1) & 1);
                    mbar_expect(fb, K3_STAGE);
                    tma2d(st, it < 10 ? &tm_wob : &tm_wm, fb, ct * 64, (it % 10) * 64);
                }
                bulk_load(st + 8192, g_acat + (size_t)(((it + 10) % 20) * 256 + tt * 20) * 1024, 20480, fb);
            }
        }
    } else {
        float acc[80];
        #pragma unroll
        for (int i = 0; i < 80; i++) acc[i] = 0.f;
        fence_f(acc);
        for (int it = 0; it < 20; it++) {
            const int s = it % K3_NST;
            mbar_wait(bar_full + 8 * s, (it / K3_NST) & 1);
            if (it == 0) CK3(2); if (it == 6) CK3(3); if (it == 12) CK3(4);
            const uint32_t st = sb + s * K3_STAGE;
            const uint64_t da = mkdesc(st, 8192, 1024, 1), db = mkdesc(st + 8192, 128, 1024, 0);
            WG_FENCE();
            #pragma unroll
            for (int k = 0; k < 4; k++) wg_ss_n160_at(acc, da + k * 128, db + k * 16, 1);
            WG_COMMIT();
            WG_WAIT(1);
            if (it > 0 && lane == 0) mbar_arrive(bar_empty + 8 * ((it - 1) % K3_NST));
        }
        WG_WAIT(0);
        fence_f(acc);
        CK3(5);
        named_bar(1, 128);
        #pragma unroll
        for (int j = 0; j < 20; j += 2) {
            const int tok = 8 * (j + (lane >> 4)) + (lane & 7);
            const int chunk = (2 * warp + ((lane >> 3) & 1)) ^ (tok & 7);
            const uint32_t addr = sb + tok * 128 + chunk * 16;
            asm volatile("stmatrix.sync.aligned.m8n8.x4.trans.shared.b16 [%0], {%1,%2,%3,%4};" :: "r"(addr),
                "r"(packbf(acc[4*j], acc[4*j+1])), "r"(packbf(acc[4*j+2], acc[4*j+3])), "r"(packbf(acc[4*j+4], acc[4*j+5])), "r"(packbf(acc[4*j+6], acc[4*j+7])) : "memory");
        }
        named_bar(1, 128);
        #pragma unroll
        for (int i = 0; i < 10; i++) {
            const int idx = tid + 128 * i, tok = idx >> 3, ch = idx & 7;
            const int gtok = tt * 160 + tok;
            const uint4 v = *(const uint4*)(smem + tok * 128 + ((ch ^ (tok & 7)) * 16));
            if (gtok < SEQ) *(uint4*)(out + (size_t)gtok * DM + ct * 64 + ch * 8) = v;
        }
        TS_MAX(10); CK3(6);
    }
}

typedef CUresult (*PFN_tmapEncode)(CUtensorMap*, CUtensorMapDataType, cuuint32_t, void*, const cuuint64_t*, const cuuint64_t*, const cuuint32_t*, const cuuint32_t*,
                                   CUtensorMapInterleave, CUtensorMapSwizzle, CUtensorMapL2promotion, CUtensorMapFloatOOBfill);
static void make_map(PFN_tmapEncode enc, CUtensorMap* tm, const void* ptr, uint64_t cols, uint64_t rows, uint32_t bcols, uint32_t brows) {
    cuuint64_t gd[2] = {cols, rows}; cuuint64_t gs[1] = {cols * 2}; cuuint32_t bx[2] = {bcols, brows}; cuuint32_t es[2] = {1, 1};
    enc(tm, CU_TENSOR_MAP_DATA_TYPE_BFLOAT16, 2, (void*)ptr, gd, gs, bx, es, CU_TENSOR_MAP_INTERLEAVE_NONE, CU_TENSOR_MAP_SWIZZLE_128B,
        CU_TENSOR_MAP_L2_PROMOTION_L2_128B, CU_TENSOR_MAP_FLOAT_OOB_FILL_NONE);
}

extern "C" void kernel_launch(void* const* d_in, const int* in_sizes, int n_in, void* d_out, int out_size) {
    const __nv_bfloat16* x = (const __nv_bfloat16*)d_in[0];
    const __nv_bfloat16* a_wqkv = (const __nv_bfloat16*)d_in[1];
    const __nv_bfloat16* a_wo = (const __nv_bfloat16*)d_in[2];
    const __nv_bfloat16* b_wqkv = (const __nv_bfloat16*)d_in[4];
    const __nv_bfloat16* b_wo = (const __nv_bfloat16*)d_in[5];
    const __nv_bfloat16* gate_w = (const __nv_bfloat16*)d_in[6];
    static CUtensorMap tm_x, tm_wm, tm_wob;
    static WMaps tm_w;
    static const void* cached[4] = {nullptr, nullptr, nullptr, nullptr};
    if (cached[0] != x || cached[1] != a_wqkv || cached[2] != b_wqkv || cached[3] != b_wo) {
        void* fn = nullptr; cudaDriverEntryPointQueryResult qr;
        cudaGetDriverEntryPoint("cuTensorMapEncodeTiled", &fn, cudaEnableDefault, &qr);
        PFN_tmapEncode enc = (PFN_tmapEncode)fn;
        void* p_wm;
        cudaGetSymbolAddress(&p_wm, g_wm);
        make_map(enc, &tm_x, x, DM, SEQ, 64, 128);
        for (int i = 0; i < 4; i++) {
            cuuint64_t gd[4] = {64, DM, 10, 3}; cuuint64_t gs[3] = {3 * DM * 2, 128, DM * 2};
            cuuint32_t bx[4] = {64, 64, 3, (cuuint32_t)((i & 1) ? 1 : 2)}; cuuint32_t es[4] = {1, 1, 1, 1};
            enc(&tm_w.m[i], CU_TENSOR_MAP_DATA_TYPE_BFLOAT16, 4, (void*)(i < 2 ? a_wqkv : b_wqkv), gd, gs, bx, es, CU_TENSOR_MAP_INTERLEAVE_NONE,
                CU_TENSOR_MAP_SWIZZLE_128B, CU_TENSOR_MAP_L2_PROMOTION_L2_128B, CU_TENSOR_MAP_FLOAT_OOB_FILL_NONE);
        }
        make_map(enc, &tm_wm, p_wm, DM, DM, 64, 64);
        make_map(enc, &tm_wob, b_wo, DM, DM, 64, 64);
        cudaFuncSetAttribute(qkv_kernel, cudaFuncAttributeMaxDynamicSharedMemorySize, K1_SMEM);
        cudaFuncSetAttribute(attn_kernel, cudaFuncAttributeMaxDynamicSharedMemorySize, K2_SMEM);
        cudaFuncSetAttribute(out_kernel, cudaFuncAttributeMaxDynamicSharedMemorySize, K3_SMEM);
        cached[0] = x; cached[1] = a_wqkv; cached[2] = b_wqkv; cached[3] = b_wo;
    }
    cudaStream_t st = cudaStreamPerThread;
    cudaLaunchAttribute at[1];
    at[0].id = cudaLaunchAttributeProgrammaticStreamSerialization; at[0].val.programmaticStreamSerializationAllowed = 1;
    cudaLaunchConfig_t cfg = {};
    cfg.stream = st;
    cfg.gridDim = dim3(128); cfg.blockDim = dim3(512); cfg.dynamicSmemBytes = K1_SMEM; cfg.attrs = at; cfg.numAttrs = 0;
    cudaLaunchKernelEx(&cfg, qkv_kernel, tm_x, tm_w, x, gate_w);
    cfg.gridDim = dim3(132); cfg.blockDim = dim3(512); cfg.dynamicSmemBytes = K2_SMEM; cfg.numAttrs = 1;
    cudaLaunchKernelEx(&cfg, attn_kernel, a_wo);
    cfg.gridDim = dim3(130); cfg.blockDim = dim3(160); cfg.dynamicSmemBytes = K3_SMEM; cfg.numAttrs = 1;
    cudaLaunchKernelEx(&cfg, out_kernel, tm_wm, tm_wob, (__nv_bfloat16*)d_out);
}
```

```cpp
#include <cuda_runtime.h>
#include <cuda_bf16.h>
#include <cuda.h>
#include <stdint.h>

#define SEQ 2048
#define DM 640
#define NH 32
#define DH 20

#define POLY_MASK 0xD5DDu

__device__ __align__(1024) uint8_t g_kvimg[NH * 196608];
__device__ __align__(1024) uint8_t g_qb[SEQ * DM * 2];
__device__ __align__(1024) uint8_t g_pq[SEQ * DM * 2];
__device__ __align__(1024) uint8_t g_acat[SEQ * 2 * DM * 2 + 4096];
__device__ __align__(1024) __nv_bfloat16 g_wm[DM * DM];
__device__ __align__(16) float g_kvpart[16 * NH * 480];
__device__ __align__(16) float g_zpart[16 * NH * 20];
__device__ __align__(16) float g_kn2[NH * 128];
__device__ __align__(16) float g_gate[SEQ];

__device__ __forceinline__ uint32_t smem_u32(const void* p) { return (uint32_t)__cvta_generic_to_shared(p); }
__device__ __forceinline__ uint64_t mkdesc(uint32_t saddr, uint32_t lbo, uint32_t sbo, uint32_t swz) {
    return (uint64_t)((saddr & 0x3FFFF) >> 4) | ((uint64_t)(lbo >> 4) << 16) | ((uint64_t)(sbo >> 4) << 32) | ((uint64_t)swz << 62);
}
#define WG_FENCE() asm volatile("wgmma.fence.sync.aligned;" ::: "memory")
#define WG_COMMIT() asm volatile("wgmma.commit_group.sync.aligned;" ::: "memory")
#define WG_WAIT(n) asm volatile("wgmma.wait_group.sync.aligned %0;" :: "n"(n) : "memory")
template<int N> __device__ __forceinline__ void fence_f(float (&d)[N]) {
    #pragma unroll
    for (int i = 0; i < N; i++) asm volatile("" : "+f"(d[i]) :: "memory");
}
template<int N> __device__ __forceinline__ void fence_r(uint32_t (&d)[N]) {
    #pragma unroll
    for (int i = 0; i < N; i++) asm volatile("" : "+r"(d[i]) :: "memory");
}
__device__ __forceinline__ void mbar_init(uint32_t bar, uint32_t cnt) { asm volatile("mbarrier.init.shared::cta.b64 [%0], %1;" :: "r"(bar), "r"(cnt)); }
__device__ __forceinline__ void mbar_expect(uint32_t bar, uint32_t bytes) { asm volatile("mbarrier.arrive.expect_tx.shared::cta.b64 _, [%0], %1;" :: "r"(bar), "r"(bytes) : "memory"); }
__device__ __forceinline__ void mbar_arrive(uint32_t bar) { asm volatile("mbarrier.arrive.shared::cta.b64 _, [%0];" :: "r"(bar) : "memory"); }
__device__ __forceinline__ void mbar_wait(uint32_t bar, uint32_t parity) {
    asm volatile("{\n.reg .pred p;\nWAIT_%=:\nmbarrier.try_wait.parity.shared::cta.b64 p, [%0], %1;\n@p bra DONE_%=;\nbra WAIT_%=;\nDONE_%=:\n}" :: "r"(bar), "r"(parity) : "memory");
}
__device__ __forceinline__ void tma2d(uint32_t dst, const CUtensorMap* tm, uint32_t bar, int c0, int c1) {
    asm volatile("cp.async.bulk.tensor.2d.shared::cluster.global.mbarrier::complete_tx::bytes [%0], [%1, {%3,%4}], [%2];"
        :: "r"(dst), "l"((uint64_t)tm), "r"(bar), "r"(c0), "r"(c1) : "memory");
}
__device__ __forceinline__ void bulk_load(uint32_t dst, const void* src, uint32_t bytes, uint32_t bar) {
    asm volatile("cp.async.bulk.shared::cluster.global.mbarrier::complete_tx::bytes [%0], [%1], %2, [%3];" :: "r"(dst), "l"(src), "r"(bytes), "r"(bar) : "memory");
}
__device__ __forceinline__ void named_bar(int id, int n) { asm volatile("bar.sync %0, %1;" :: "r"(id), "r"(n) : "memory"); }
__device__ __forceinline__ float ex2f(float x) { float y; asm("ex2.approx.ftz.f32 %0, %1;" : "=f"(y) : "f"(x)); return y; }
__device__ __forceinline__ uint32_t packbf(float lo, float hi) { uint32_t r; asm("cvt.rn.bf16x2.f32 %0, %1, %2;" : "=r"(r) : "f"(hi), "f"(lo)); return r; }
__device__ __forceinline__ float bflo(uint32_t v) { return __uint_as_float(v << 16); }
__device__ __forceinline__ float bfhi(uint32_t v) { return __uint_as_float(v & 0xFFFF0000u); }
__device__ __forceinline__ float bfr(float v) { return bflo(packbf(v, 0.f)); }
__device__ __forceinline__ float dot_bf(uint32_t a, uint32_t b) {
    uint32_t p; asm("mul.rn.bf16x2 %0, %1, %2;" : "=r"(p) : "r"(a), "r"(b));
    return bflo(p) + bfhi(p);
}
__device__ __forceinline__ float phi_f(float t) { return (fmaxf(t, 0.f) + 1e-6f) + ex2f(fminf(t, 0.f) * 1.4426950408889634f); }
#define GRIDDEP_WAIT() asm volatile("griddepcontrol.wait;" ::: "memory")
#define GRIDDEP_LAUNCH() asm volatile("griddepcontrol.launch_dependents;" ::: "memory")

__device__ __forceinline__ void wg_rs_n128_bt(float (&d)[64], uint32_t a0, uint32_t a1, uint32_t a2, uint32_t a3, uint64_t db) {
    asm volatile("wgmma.mma_async.sync.aligned.m64n128k16.f32.bf16.bf16 {%0,%1,%2,%3,%4,%5,%6,%7,%8,%9,%10,%11,%12,%13,%14,%15,%16,%17,%18,%19,%20,%21,%22,%23,%24,%25,%26,%27,%28,%29,%30,%31,%32,%33,%34,%35,%36,%37,%38,%39,%40,%41,%42,%43,%44,%45,%46,%47,%48,%49,%50,%51,%52,%53,%54,%55,%56,%57,%58,%59,%60,%61,%62,%63}, {%64,%65,%66,%67}, %68, 1, 1, 1, 1;"
      : "+f"(d[0]),"+f"(d[1]),"+f"(d[2]),"+f"(d[3]),"+f"(d[4]),"+f"(d[5]),"+f"(d[6]),"+f"(d[7]),"+f"(d[8]),"+f"(d[9]),"+f"(d[10]),"+f"(d[11]),"+f"(d[12]),"+f"(d[13]),"+f"(d[14]),"+f"(d[15]),"+f"(d[16]),"+f"(d[17]),"+f"(d[18]),"+f"(d[19]),"+f"(d[20]),"+f"(d[21]),"+f"(d[22]),"+f"(d[23]),"+f"(d[24]),"+f"(d[25]),"+f"(d[26]),"+f"(d[27]),"+f"(d[28]),"+f"(d[29]),"+f"(d[30]),"+f"(d[31]),"+f"(d[32]),"+f"(d[33]),"+f"(d[34]),"+f"(d[35]),"+f"(d[36]),"+f"(d[37]),"+f"(d[38]),"+f"(d[39]),"+f"(d[40]),"+f"(d[41]),"+f"(d[42]),"+f"(d[43]),"+f"(d[44]),"+f"(d[45]),"+f"(d[46]),"+f"(d[47]),"+f"(d[48]),"+f"(d[49]),"+f"(d[50]),"+f"(d[51]),"+f"(d[52]),"+f"(d[53]),"+f"(d[54]),"+f"(d[55]),"+f"(d[56]),"+f"(d[57]),"+f"(d[58]),"+f"(d[59]),"+f"(d[60]),"+f"(d[61]),"+f"(d[62]),"+f"(d[63]) : "r"(a0), "r"(a1), "r"(a2), "r"(a3), "l"(db));
}
__device__ __forceinline__ void wg_ss_n64_bt(float (&d)[32], uint64_t da, uint64_t db, int acc) {
    asm volatile("{.reg .pred p; setp.ne.b32 p, %34, 0;\n"
      "wgmma.mma_async.sync.aligned.m64n64k16.f32.bf16.bf16 {%0,%1,%2,%3,%4,%5,%6,%7,%8,%9,%10,%11,%12,%13,%14,%15,%16,%17,%18,%19,%20,%21,%22,%23,%24,%25,%26,%27,%28,%29,%30,%31}, %32, %33, p, 1, 1, 0, 1;}"
      : "+f"(d[0]),"+f"(d[1]),"+f"(d[2]),"+f"(d[3]),"+f"(d[4]),"+f"(d[5]),"+f"(d[6]),"+f"(d[7]),"+f"(d[8]),"+f"(d[9]),"+f"(d[10]),"+f"(d[11]),"+f"(d[12]),"+f"(d[13]),"+f"(d[14]),"+f"(d[15]),"+f"(d[16]),"+f"(d[17]),"+f"(d[18]),"+f"(d[19]),"+f"(d[20]),"+f"(d[21]),"+f"(d[22]),"+f"(d[23]),"+f"(d[24]),"+f"(d[25]),"+f"(d[26]),"+f"(d[27]),"+f"(d[28]),"+f"(d[29]),"+f"(d[30]),"+f"(d[31]) : "l"(da), "l"(db), "r"(acc));
}
__device__ __forceinline__ void wg_ss_n32_bt(float (&d)[16], uint64_t da, uint64_t db, int acc) {
    asm volatile("{.reg .pred p; setp.ne.b32 p, %18, 0;\n"
      "wgmma.mma_async.sync.aligned.m64n32k16.f32.bf16.bf16 {%0,%1,%2,%3,%4,%5,%6,%7,%8,%9,%10,%11,%12,%13,%14,%15}, %16, %17, p, 1, 1, 0, 1;}"
      : "+f"(d[0]),"+f"(d[1]),"+f"(d[2]),"+f"(d[3]),"+f"(d[4]),"+f"(d[5]),"+f"(d[6]),"+f"(d[7]),"+f"(d[8]),"+f"(d[9]),"+f"(d[10]),"+f"(d[11]),"+f"(d[12]),"+f"(d[13]),"+f"(d[14]),"+f"(d[15]) : "l"(da), "l"(db), "r"(acc));
}
__device__ __forceinline__ void wg_rs_n32_bt(float (&d)[16], uint32_t a0, uint32_t a1, uint32_t a2, uint32_t a3, uint64_t db) {
    asm volatile("wgmma.mma_async.sync.aligned.m64n32k16.f32.bf16.bf16 {%0,%1,%2,%3,%4,%5,%6,%7,%8,%9,%10,%11,%12,%13,%14,%15}, {%16,%17,%18,%19}, %20, 1, 1, 1, 1;"
      : "+f"(d[0]),"+f"(d[1]),"+f"(d[2]),"+f"(d[3]),"+f"(d[4]),"+f"(d[5]),"+f"(d[6]),"+f"(d[7]),"+f"(d[8]),"+f"(d[9]),"+f"(d[10]),"+f"(d[11]),"+f"(d[12]),"+f"(d[13]),"+f"(d[14]),"+f"(d[15]) : "r"(a0), "r"(a1), "r"(a2), "r"(a3), "l"(db));
}
__device__ __forceinline__ void wg_ss_n88_atbt(float (&d)[44], uint64_t da, uint64_t db, int acc) {
    asm volatile("{.reg .pred p; setp.ne.b32 p, %46, 0;\n"
      "wgmma.mma_async.sync.aligned.m64n88k16.f32.bf16.bf16 {%0,%1,%2,%3,%4,%5,%6,%7,%8,%9,%10,%11,%12,%13,%14,%15,%16,%17,%18,%19,%20,%21,%22,%23,%24,%25,%26,%27,%28,%29,%30,%31,%32,%33,%34,%35,%36,%37,%38,%39,%40,%41,%42,%43}, %44, %45, p, 1, 1, 1, 1;}"
      : "+f"(d[0]),"+f"(d[1]),"+f"(d[2]),"+f"(d[3]),"+f"(d[4]),"+f"(d[5]),"+f"(d[6]),"+f"(d[7]),"+f"(d[8]),"+f"(d[9]),"+f"(d[10]),"+f"(d[11]),"+f"(d[12]),"+f"(d[13]),"+f"(d[14]),"+f"(d[15]),"+f"(d[16]),"+f"(d[17]),"+f"(d[18]),"+f"(d[19]),"+f"(d[20]),"+f"(d[21]),"+f"(d[22]),"+f"(d[23]),"+f"(d[24]),"+f"(d[25]),"+f"(d[26]),"+f"(d[27]),"+f"(d[28]),"+f"(d[29]),"+f"(d[30]),"+f"(d[31]),"+f"(d[32]),"+f"(d[33]),"+f"(d[34]),"+f"(d[35]),"+f"(d[36]),"+f"(d[37]),"+f"(d[38]),"+f"(d[39]),"+f"(d[40]),"+f"(d[41]),"+f"(d[42]),"+f"(d[43]) : "l"(da), "l"(db), "r"(acc));
}
__device__ __forceinline__ void wg_ss_n8_atbt(float (&d)[4], uint64_t da, uint64_t db, int acc) {
    asm volatile("{.reg .pred p; setp.ne.b32 p, %6, 0;\n"
      "wgmma.mma_async.sync.aligned.m64n8k16.f32.bf16.bf16 {%0,%1,%2,%3}, %4, %5, p, 1, 1, 1, 1;}"
      : "+f"(d[0]),"+f"(d[1]),"+f"(d[2]),"+f"(d[3]) : "l"(da), "l"(db), "r"(acc));
}
__device__ __forceinline__ void wg_ss_n160_at(float (&d)[80], uint64_t da, uint64_t db, int acc) {
    asm volatile("{.reg .pred p; setp.ne.b32 p, %82, 0;\n"
      "wgmma.mma_async.sync.aligned.m64n160k16.f32.bf16.bf16 {%0,%1,%2,%3,%4,%5,%6,%7,%8,%9,%10,%11,%12,%13,%14,%15,%16,%17,%18,%19,%20,%21,%22,%23,%24,%25,%26,%27,%28,%29,%30,%31,%32,%33,%34,%35,%36,%37,%38,%39,%40,%41,%42,%43,%44,%45,%46,%47,%48,%49,%50,%51,%52,%53,%54,%55,%56,%57,%58,%59,%60,%61,%62,%63,%64,%65,%66,%67,%68,%69,%70,%71,%72,%73,%74,%75,%76,%77,%78,%79}, %80, %81, p, 1, 1, 1, 0;}"
      : "+f"(d[0]),"+f"(d[1]),"+f"(d[2]),"+f"(d[3]),"+f"(d[4]),"+f"(d[5]),"+f"(d[6]),"+f"(d[7]),"+f"(d[8]),"+f"(d[9]),"+f"(d[10]),"+f"(d[11]),"+f"(d[12]),"+f"(d[13]),"+f"(d[14]),"+f"(d[15]),"+f"(d[16]),"+f"(d[17]),"+f"(d[18]),"+f"(d[19]),"+f"(d[20]),"+f"(d[21]),"+f"(d[22]),"+f"(d[23]),"+f"(d[24]),"+f"(d[25]),"+f"(d[26]),"+f"(d[27]),"+f"(d[28]),"+f"(d[29]),"+f"(d[30]),"+f"(d[31]),"+f"(d[32]),"+f"(d[33]),"+f"(d[34]),"+f"(d[35]),"+f"(d[36]),"+f"(d[37]),"+f"(d[38]),"+f"(d[39]),"+f"(d[40]),"+f"(d[41]),"+f"(d[42]),"+f"(d[43]),"+f"(d[44]),"+f"(d[45]),"+f"(d[46]),"+f"(d[47]),"+f"(d[48]),"+f"(d[49]),"+f"(d[50]),"+f"(d[51]),"+f"(d[52]),"+f"(d[53]),"+f"(d[54]),"+f"(d[55]),"+f"(d[56]),"+f"(d[57]),"+f"(d[58]),"+f"(d[59]),"+f"(d[60]),"+f"(d[61]),"+f"(d[62]),"+f"(d[63]),"+f"(d[64]),"+f"(d[65]),"+f"(d[66]),"+f"(d[67]),"+f"(d[68]),"+f"(d[69]),"+f"(d[70]),"+f"(d[71]),"+f"(d[72]),"+f"(d[73]),"+f"(d[74]),"+f"(d[75]),"+f"(d[76]),"+f"(d[77]),"+f"(d[78]),"+f"(d[79]) : "l"(da), "l"(db), "r"(acc));
}
__device__ __forceinline__ void wg_qk0(float (&d)[32], uint32_t a0, uint32_t a1, uint32_t a2, uint32_t a3, uint64_t db) {
    asm volatile("wgmma.mma_async.sync.aligned.m64n64k16.f32.bf16.bf16 {%0,%1,%2,%3,%4,%5,%6,%7,%8,%9,%10,%11,%12,%13,%14,%15,%16,%17,%18,%19,%20,%21,%22,%23,%24,%25,%26,%27,%28,%29,%30,%31}, {%32,%33,%34,%35}, %36, 0, 1, 1, 0;"
      : "+f"(d[0]),"+f"(d[1]),"+f"(d[2]),"+f"(d[3]),"+f"(d[4]),"+f"(d[5]),"+f"(d[6]),"+f"(d[7]),"+f"(d[8]),"+f"(d[9]),"+f"(d[10]),"+f"(d[11]),"+f"(d[12]),"+f"(d[13]),"+f"(d[14]),"+f"(d[15]),"+f"(d[16]),"+f"(d[17]),"+f"(d[18]),"+f"(d[19]),"+f"(d[20]),"+f"(d[21]),"+f"(d[22]),"+f"(d[23]),"+f"(d[24]),"+f"(d[25]),"+f"(d[26]),"+f"(d[27]),"+f"(d[28]),"+f"(d[29]),"+f"(d[30]),"+f"(d[31]) : "r"(a0), "r"(a1), "r"(a2), "r"(a3), "l"(db));
}
__device__ __forceinline__ void wg_qk1(float (&d)[32], uint32_t a0, uint32_t a1, uint32_t a2, uint32_t a3, uint64_t db) {
    asm volatile("wgmma.mma_async.sync.aligned.m64n64k16.f32.bf16.bf16 {%0,%1,%2,%3,%4,%5,%6,%7,%8,%9,%10,%11,%12,%13,%14,%15,%16,%17,%18,%19,%20,%21,%22,%23,%24,%25,%26,%27,%28,%29,%30,%31}, {%32,%33,%34,%35}, %36, 1, 1, 1, 0;"
      : "+f"(d[0]),"+f"(d[1]),"+f"(d[2]),"+f"(d[3]),"+f"(d[4]),"+f"(d[5]),"+f"(d[6]),"+f"(d[7]),"+f"(d[8]),"+f"(d[9]),"+f"(d[10]),"+f"(d[11]),"+f"(d[12]),"+f"(d[13]),"+f"(d[14]),"+f"(d[15]),"+f"(d[16]),"+f"(d[17]),"+f"(d[18]),"+f"(d[19]),"+f"(d[20]),"+f"(d[21]),"+f"(d[22]),"+f"(d[23]),"+f"(d[24]),"+f"(d[25]),"+f"(d[26]),"+f"(d[27]),"+f"(d[28]),"+f"(d[29]),"+f"(d[30]),"+f"(d[31]) : "r"(a0), "r"(a1), "r"(a2), "r"(a3), "l"(db));
}
__device__ __forceinline__ void wg_pv(float (&d)[12], uint32_t a0, uint32_t a1, uint32_t a2, uint32_t a3, uint64_t db) {
    asm volatile("wgmma.mma_async.sync.aligned.m64n24k16.f32.bf16.bf16 {%0,%1,%2,%3,%4,%5,%6,%7,%8,%9,%10,%11}, {%12,%13,%14,%15}, %16, 1, 1, 1, 1;"
      : "+f"(d[0]),"+f"(d[1]),"+f"(d[2]),"+f"(d[3]),"+f"(d[4]),"+f"(d[5]),"+f"(d[6]),"+f"(d[7]),"+f"(d[8]),"+f"(d[9]),"+f"(d[10]),"+f"(d[11]) : "r"(a0), "r"(a1), "r"(a2), "r"(a3), "l"(db));
}

#define K1_ONES 204800
#define K1_BARS 205056
#define K1_SMEM 205312
#define QSCALE 0.32259799f
#define K1_BAR(i) (sb + K1_BARS + 8 * (i))

__device__ __forceinline__ void tma4d(uint32_t dst, const CUtensorMap* tm, uint32_t bar, int c0, int c1, int c2, int c3) {
    asm volatile("cp.async.bulk.tensor.4d.shared::cluster.global.mbarrier::complete_tx::bytes [%0], [%1, {%3,%4,%5,%6}], [%2];"
        :: "r"(dst), "l"((uint64_t)tm), "r"(bar), "r"(c0), "r"(c1), "r"(c2), "r"(c3) : "memory");
}
__device__ __forceinline__ void k1_issue(int pass, int kb, uint32_t sb, const CUtensorMap* tx, const CUtensorMap* tw, int mt, int hg) {
    const int s = pass ? kb % 5 : kb % 3;
    const uint32_t st = sb + (pass ? s * 40960 : s * 65536), fb = K1_BAR(pass ? s : 10 + s);
    mbar_expect(fb, pass ? 40960 : 65536);
    tma2d(st, tx, fb, kb * 64, mt * 128);
    tma4d(st + 16384, tw + pass, fb, 0, kb * 64, (hg * 160) >> 6, 1 - pass);
}
__device__ __forceinline__ void stsm4(uint32_t addr, uint32_t r0, uint32_t r1, uint32_t r2, uint32_t r3) {
    asm volatile("stmatrix.sync.aligned.m8n8.x4.shared.b16 [%0], {%1,%2,%3,%4};" :: "r"(addr), "r"(r0), "r"(r1), "r"(r2), "r"(r3) : "memory");
}
__device__ __forceinline__ void bulk_store(void* dst, uint32_t src, uint32_t bytes) {
    asm volatile("cp.async.bulk.global.shared::cta.bulk_group [%0], [%1], %2;" :: "l"(dst), "r"(src), "r"(bytes) : "memory");
}
#define FENCE_ASYNC() asm volatile("fence.proxy.async.shared::cta;" ::: "memory")

__device__ __forceinline__ void k1_stage_rows(const uint32_t (&pk)[40], uint32_t base, bool odd) {
    const uint32_t b0 = base + (odd ? 512 : 0), b2 = base + (odd ? 0 : 2048);
    #pragma unroll
    for (int j = 0; j < 16; j += 2) stsm4(b0 + j * 128, pk[2*j], pk[2*j+1], pk[2*j+2], pk[2*j+3]);
    #pragma unroll
    for (int j = 0; j < 4; j += 2) stsm4(b2 + j * 128, pk[32 + 2*j], pk[33 + 2*j], pk[34 + 2*j], pk[35 + 2*j]);
}
template<bool ODD>
__device__ __forceinline__ void k1_image(const uint32_t (&pk)[40], uint32_t base, int lane) {
    #define PH(j) (ODD ? ((j) < 4 ? (j) + 16 : (j) - 4) : (j))
    const bool hi = lane & 16;
    #pragma unroll
    for (int i = 0; i < 4; i++) {
        const uint32_t e = base + (2 * i) * 12288, o = e + 12288;
        const int j = 5 * i;
        stsm4(hi ? e + 128 : e, pk[2*PH(j)], pk[2*PH(j)+1], pk[2*PH(j+1)], pk[2*PH(j+1)+1]);
        stsm4(hi ? o : e + 256, pk[2*PH(j+2)], pk[2*PH(j+2)+1], pk[2*PH(j+2)], pk[2*PH(j+2)+1]);
        stsm4(hi ? o + 256 : o + 128, pk[2*PH(j+3)], pk[2*PH(j+3)+1], pk[2*PH(j+4)], pk[2*PH(j+4)+1]);
    }
}
template<bool ODD>
__device__ __forceinline__ void k1_norms(const uint32_t (&pk)[40], int lane, float* kn_dst) {
    {
        const bool lo = (lane & 3) < 2;
        #pragma unroll
        for (int h = 0; h < 8; h++) {
            float a = 0.f, b = 0.f;
            #pragma unroll
            for (int jj = 0; jj < 3; jj++) {
                const int j = (5 * h) / 2 + jj;
                const uint32_t v0 = pk[2*PH(j)], v1 = pk[2*PH(j)+1];
                float s0 = bflo(v0) * bflo(v0) + bfhi(v0) * bfhi(v0), s1 = bflo(v1) * bflo(v1) + bfhi(v1) * bfhi(v1);
                if (jj == ((h & 1) ? 0 : 2)) { const bool mine = (h & 1) ? !lo : lo; s0 = mine ? s0 : 0.f; s1 = mine ? s1 : 0.f; }
                a += s0; b += s1;
            }
            a += __shfl_xor_sync(0xffffffffu, a, 1); b += __shfl_xor_sync(0xffffffffu, b, 1);
            a += __shfl_xor_sync(0xffffffffu, a, 2); b += __shfl_xor_sync(0xffffffffu, b, 2);
            a = fmaxf(a, b);
            a = fmaxf(a, __shfl_xor_sync(0xffffffffu, a, 4));
            a = fmaxf(a, __shfl_xor_sync(0xffffffffu, a, 8));
            a = fmaxf(a, __shfl_xor_sync(0xffffffffu, a, 16));
            if (lane == h) kn_dst[h * 128] = a;
        }
    }
    #undef PH
}

struct WMaps { CUtensorMap m[4]; };
__global__ void __launch_bounds__(512, 1)
qkv_kernel(const __grid_constant__ CUtensorMap tm_x, const __grid_constant__ WMaps tm_w,
           const __nv_bfloat16* __restrict__ x, const __nv_bfloat16* __restrict__ gate_w) {
    extern __shared__ __align__(1024) uint8_t smem[];
    const uint32_t sb = smem_u32(smem);
    const int tid = threadIdx.x, warp = tid >> 5, lane = tid & 31;
    const int mt = ((blockIdx.x >> 4) & 3) * 4 + (blockIdx.x & 3), grp = (blockIdx.x >> 6) * 4 + ((blockIdx.x >> 2) & 3), br = grp >> 2, hg = grp & 3;
    const CUtensorMap* tw = &tm_w.m[br * 2];
        if (tid == 0) {
        for (int i = 0; i < 5; i++) { mbar_init(K1_BAR(i), 1); mbar_init(K1_BAR(5 + i), 16); }
        for (int i = 0; i < 3; i++) { mbar_init(K1_BAR(10 + i), 1); mbar_init(K1_BAR(13 + i), 16); }
        mbar_init(K1_BAR(16), 16); mbar_init(K1_BAR(17), 16); mbar_init(K1_BAR(18), 12);
        asm volatile("fence.mbarrier_init.release.cluster;" ::: "memory");
        k1_issue(1, 0, sb, &tm_x, tw, mt, hg);
    }
    __syncthreads();
    GRIDDEP_LAUNCH();
    if (tid == 0) for (int i = 1; i < 5; i++) k1_issue(1, i, sb, &tm_x, tw, mt, hg);
    if (tid >= 64 && tid < 96) *(uint32_t*)(smem + K1_ONES + lane * 4) = (lane & 3) == 0 ? 0x3F80u : 0u;
    __syncwarp();
    const int wg = __shfl_sync(0xffffffffu, warp >> 2, 0), mh = wg & 1, sel = wg >> 1, w4 = warp & 3;
    const int g = lane >> 2, t = lane & 3;
    const bool odd = hg & 1;
    {
        float a0[32], a2[16];
        #pragma unroll
        for (int i = 0; i < 32; i++) a0[i] = 0.f;
        #pragma unroll
        for (int i = 0; i < 16; i++) a2[i] = 0.f;
        fence_f(a0); fence_f(a2);
        const uint32_t o0 = sel ? 512 : (odd ? 1024 : 0), o2 = odd ? 4 : 1024;
        for (int kb = 0; kb < 10; kb++) {
            const int s = kb % 5;
            mbar_wait(K1_BAR(s), kb >= 5);
            const uint32_t st = sb + s * 40960;
            const uint64_t da = mkdesc(st + mh * 8192, 16, 1024, 1), db = mkdesc(st + 16384, 8192, 1024, 1);
            WG_FENCE();
            #pragma unroll
            for (int k = 0; k < 4; k++) wg_ss_n64_bt(a0, da + k * 2, db + o0 + k * 128, 1);
            if (sel) {
                #pragma unroll
                for (int k = 0; k < 4; k++) wg_ss_n32_bt(a2, da + k * 2, db + o2 + k * 128, 1);
            }
            WG_COMMIT();
            WG_WAIT(0);
            if (lane == 0) mbar_arrive(K1_BAR(5 + s));
            if (tid == 0) {
                mbar_wait(K1_BAR(5 + s), kb >= 5);
                if (kb < 5) k1_issue(1, kb + 5, sb, &tm_x, tw, mt, hg);
                else if (kb == 6) k1_issue(0, 0, sb, &tm_x, tw, mt, hg);
                else if (kb >= 8) k1_issue(0, kb - 7, sb, &tm_x, tw, mt, hg);
            }
            __syncwarp();
        }
        fence_f(a0); fence_f(a2);
        uint8_t* dst = (br ? g_qb : g_pq) + ((mt * 16 + mh * 8 + w4 * 2) * 80 + hg * 20) * 128 + lane * 4;
        uint8_t* d0 = dst + (sel ? (odd ? 4 : 8) : (odd ? 12 : 0)) * 128;
        uint8_t* d2 = dst + (odd ? 0 : 16) * 128;
        if (br) {
            #pragma unroll
            for (int j = 0; j < 8; j++) {
                *(uint32_t*)(d0 + j * 128) = packbf(a0[4*j] * QSCALE, a0[4*j+1] * QSCALE);
                *(uint32_t*)(d0 + 10240 + j * 128) = packbf(a0[4*j+2] * QSCALE, a0[4*j+3] * QSCALE);
            }
            if (sel) {
                #pragma unroll
                for (int j = 0; j < 4; j++) {
                    *(uint32_t*)(d2 + j * 128) = packbf(a2[4*j] * QSCALE, a2[4*j+1] * QSCALE);
                    *(uint32_t*)(d2 + 10240 + j * 128) = packbf(a2[4*j+2] * QSCALE, a2[4*j+3] * QSCALE);
                }
            }
        } else {
            #pragma unroll
            for (int j = 0; j < 8; j++) {
                *(uint32_t*)(d0 + j * 128) = packbf(phi_f(a0[4*j]), phi_f(a0[4*j+1]));
                *(uint32_t*)(d0 + 10240 + j * 128) = packbf(phi_f(a0[4*j+2]), phi_f(a0[4*j+3]));
            }
            if (sel) {
                #pragma unroll
                for (int j = 0; j < 4; j++) {
                    *(uint32_t*)(d2 + j * 128) = packbf(phi_f(a2[4*j]), phi_f(a2[4*j+1]));
                    *(uint32_t*)(d2 + 10240 + j * 128) = packbf(phi_f(a2[4*j+2]), phi_f(a2[4*j+3]));
                }
            }
        }
    }
    uint32_t pk[40];
    {
        float a0[64], a2[16];
        #pragma unroll
        for (int i = 0; i < 64; i++) a0[i] = 0.f;
        #pragma unroll
        for (int i = 0; i < 16; i++) a2[i] = 0.f;
        fence_f(a0); fence_f(a2);
        const uint32_t o0 = odd ? 512 : 0, o2 = odd ? 4 : 1024;
        const uint32_t arow = (mh * 64 + w4 * 16 + (lane & 15)) * 128;
        for (int kb = 0; kb < 10; kb++) {
            const int s = kb % 3;
            mbar_wait(K1_BAR(10 + s), (kb / 3) & 1);
            const uint32_t st = sb + s * 65536;
            const uint64_t db = mkdesc(st + 16384 + sel * 24576, 8192, 1024, 1);
            uint32_t af[4][4];
            #pragma unroll
            for (int k = 0; k < 4; k++)
                asm volatile("ldmatrix.sync.aligned.m8n8.x4.shared.b16 {%0,%1,%2,%3}, [%4];"
                    : "=r"(af[k][0]), "=r"(af[k][1]), "=r"(af[k][2]), "=r"(af[k][3]) : "r"(st + arow + (((2 * k + (lane >> 4)) ^ (lane & 7)) << 4)));
            WG_FENCE();
            #pragma unroll
            for (int k = 0; k < 4; k++) {
                wg_rs_n128_bt(a0, af[k][0], af[k][1], af[k][2], af[k][3], db + o0 + k * 128);
                wg_rs_n32_bt(a2, af[k][0], af[k][1], af[k][2], af[k][3], db + o2 + k * 128);
            }
            WG_COMMIT();
            WG_WAIT(0);
            const uint32_t eb = K1_BAR(kb == 9 ? 16 : 13 + s);
            if (lane == 0) mbar_arrive(eb);
            if (tid == 0 && kb < 7) { mbar_wait(eb, (kb / 3) & 1); k1_issue(0, kb + 3, sb, &tm_x, tw, mt, hg); }
            __syncwarp();
        }
        fence_f(a0); fence_f(a2);
        if (br == 0 && sel == 0) {
            #pragma unroll
            for (int i = 0; i < 32; i++) pk[i] = packbf(phi_f(a0[2 * i]), phi_f(a0[2 * i + 1]));
            #pragma unroll
            for (int i = 0; i < 8; i++) pk[32 + i] = packbf(phi_f(a2[2 * i]), phi_f(a2[2 * i + 1]));
        } else {
            #pragma unroll
            for (int i = 0; i < 32; i++) pk[i] = packbf(a0[2 * i], a0[2 * i + 1]);
            #pragma unroll
            for (int i = 0; i < 8; i++) pk[32 + i] = packbf(a2[2 * i], a2[2 * i + 1]);
        }
    }
    const int rg = mh * 8 + w4 * 2 + ((lane >> 3) & 1);
    mbar_wait(K1_BAR(14), 0); mbar_wait(K1_BAR(15), 0);
    const uint32_t stg = sb + 65536;
    bool do_gate;
    if (br) {
        const uint32_t base = stg + rg * 768 + sel * 384 + (lane & 7) * 16;
        if (odd) k1_image<true>(pk, base, lane); else k1_image<false>(pk, base, lane);
        __syncwarp();
        {
            const int lr = mh * 64 + w4 * 16 + (lane & 15);
            const uint32_t flag = (sel == 0 && ((POLY_MASK >> ((lr >> 3) & 15)) & 1)) ? 0x3F80u : 0u;
            const uint2 cv = make_uint2(0x3F80u | (flag << 16), flag);
            uint8_t* p = smem + 65536 + (lane >> 4) * 49152 + (lr >> 3) * 768 + sel * 384 + (lr & 7) * 16;
            *(uint2*)(p + 264) = cv; *(uint2*)(p + 12288) = cv; *(uint2*)(p + 24576 + 264) = cv; *(uint2*)(p + 36864) = cv;
        }
        FENCE_ASYNC();
        __syncwarp();
        if (lane == 0) mbar_arrive(K1_BAR(17));
        if (warp == 8 && lane < 8) {
            mbar_wait(K1_BAR(17), 0);
            bulk_store(g_kvimg + (size_t)(hg * 8 + lane) * 196608 + mt * 12288, stg + lane * 12288, 12288);
            asm volatile("cp.async.bulk.commit_group;" ::: "memory");
        }
        __syncwarp();
        if (sel == 0) {
            float* kd = g_kn2 + (hg * 8) * 128 + mt * 8 + mh * 4 + w4;
            if (odd) k1_norms<true>(pk, lane, kd); else k1_norms<false>(pk, lane, kd);
        }
        do_gate = sel == 1;
    } else {
        k1_stage_rows(pk, stg + rg * 5120 + sel * 2560 + (lane >> 4) * 128 + (lane & 7) * 16, odd);
        FENCE_ASYNC();
        __syncwarp();
        if (lane == 0) mbar_arrive(K1_BAR(17));
        if (wg != 0) {
            const int mi = wg - 1;
            mbar_wait(K1_BAR(17), 0);
            float* kvo = (float*)(smem + 65536 + 81920);
            float kv[44], zz[4];
            #pragma unroll
            for (int i = 0; i < 44; i++) kv[i] = 0.f;
            zz[0] = zz[1] = zz[2] = zz[3] = 0.f;
            fence_f(kv); fence_f(zz);
            const int vs = mi == 0 ? 0 : (mi == 1 ? 56 : 72);
            const uint64_t da = mkdesc(stg + mi * 1024, 5120, 128, 0);
            const uint64_t db = mkdesc(stg + 2560 + (vs >> 3) * 128, 5120, 128, 0);
            const uint64_t d1 = mkdesc(sb + K1_ONES, 0, 128, 0);
            WG_FENCE();
            #pragma unroll
            for (int k = 0; k < 8; k++) {
                wg_ss_n88_atbt(kv, da + k * 640, db + k * 640, 1);
                wg_ss_n8_atbt(zz, da + k * 640, d1, 1);
            }
            WG_COMMIT();
            WG_WAIT(0);
            fence_f(kv); fence_f(zz);
            #pragma unroll
            for (int r = 0; r < 2; r++) {
                const int pc = mi * 64 + w4 * 16 + g + 8 * r;
                if (pc < 160) {
                    const int e0 = vs + 2 * t - (pc / 20) * 20;
                    #pragma unroll
                    for (int j = 0; j < 11; j++) {
                        const int e = e0 + 8 * j;
                        if (e >= 0 && e < 20) *(float2*)(kvo + pc * 24 + e) = make_float2(kv[4*j + 2*r], kv[4*j + 2*r + 1]);
                    }
                    if (t == 0) kvo[3840 + pc] = zz[2 * r];
                }
            }
            FENCE_ASYNC();
            __syncwarp();
            if (lane == 0) mbar_arrive(K1_BAR(18));
            if (tid == 256) {
                mbar_wait(K1_BAR(18), 0);
                bulk_store(g_kvpart + (size_t)(mt * NH + hg * 8) * 480, stg + 81920, 15360);
                bulk_store(g_zpart + (mt * NH + hg * 8) * 20, stg + 97280, 640);
                asm volatile("cp.async.bulk.commit_group;" ::: "memory");
            }
            __syncwarp();
        }
        do_gate = wg == 0;
    }
    if (do_gate) {
        const int nr = br ? 2 : 4;
        #pragma unroll 1
        for (int r0 = 0; r0 < nr; r0 += 2) {
            const int row = mt * 128 + grp * 16 + (warp & 7) * nr + r0;
            float s0 = 0.f, s1 = 0.f;
            uint4 v0[3], v1[3], w[3];
            #pragma unroll
            for (int c = 0; c < 3; c++) {
                const int ch = min(lane + 32 * c, 79);
                v0[c] = *(const uint4*)(x + row * DM + ch * 8); v1[c] = *(const uint4*)(x + (row + 1) * DM + ch * 8); w[c] = *(const uint4*)(gate_w + ch * 8);
            }
            if (lane >= 16) w[2] = make_uint4(0, 0, 0, 0);
            #pragma unroll
            for (int c = 0; c < 3; c++) {
                s0 += dot_bf(v0[c].x, w[c].x) + dot_bf(v0[c].y, w[c].y) + dot_bf(v0[c].z, w[c].z) + dot_bf(v0[c].w, w[c].w);
                s1 += dot_bf(v1[c].x, w[c].x) + dot_bf(v1[c].y, w[c].y) + dot_bf(v1[c].z, w[c].z) + dot_bf(v1[c].w, w[c].w);
            }
            #pragma unroll
            for (int o = 16; o; o >>= 1) { s0 += __shfl_xor_sync(0xffffffffu, s0, o); s1 += __shfl_xor_sync(0xffffffffu, s1, o); }
            if (lane < 2) g_gate[row + lane] = bfr(1.f / (1.f + __expf(-bfr(lane ? s1 : s0))));
        }
    }
    if (warp == 8) asm volatile("cp.async.bulk.wait_group.read 0;" ::: "memory");
    }

#define K2_SMEM (196608 + 12288 + 1024)

struct PolyC { uint32_t one, c2; };
__device__ __forceinline__ uint32_t hfma2bf(uint32_t a, uint32_t b, uint32_t c) { uint32_t r; asm("fma.rn.bf16x2 %0, %1, %2, %3;" : "=r"(r) : "r"(a), "r"(b), "r"(c)); return r; }
__device__ __forceinline__ uint32_t exp2_poly2(float y0, float y1, const PolyC& pc) {
    const uint32_t sch = __byte_perm(__float_as_uint(y0), __float_as_uint(y1), 0x6521);
    uint32_t m; asm("lop3.b32 %0, %1, 0x007F007F, %2, 0xEA;" : "=r"(m) : "r"(sch), "r"(pc.one));
    return hfma2bf(hfma2bf(m, pc.c2, 0xC2FDC300u), m, 0x43AA43ABu) + sch;
}
template<int PAR>
__device__ __forceinline__ void softmax_blk(const float (&s)[32], uint32_t (&p)[16], const PolyC& pc) {
    #pragma unroll
    for (int j = 0; j < 8; j++) {
        if ((POLY_MASK >> (PAR * 8 + j)) & 1) {
            p[2*j] = exp2_poly2(s[4*j], s[4*j+1], pc);
            p[2*j+1] = exp2_poly2(s[4*j+2], s[4*j+3], pc);
        } else {
            p[2*j] = packbf(ex2f(s[4*j]), ex2f(s[4*j+1]));
            p[2*j+1] = packbf(ex2f(s[4*j+2]), ex2f(s[4*j+3]));
        }
    }
}

__device__ __noinline__ void aux_work(uint8_t* smem, int ax, const __nv_bfloat16* __restrict__ a_wo) {
    float* kvs = (float*)smem;
    const int tid = threadIdx.x;
    for (int i = tid; i < 3840; i += 512) {
        float s = 0.f;
        #pragma unroll
        for (int m = 0; m < 16; m++) s += g_kvpart[(size_t)(m * NH + ax * 8) * 480 + i];
        kvs[i] = s;
    }
    __syncthreads();
    #pragma unroll 1
    for (int it = tid; it < 8 * 5 * 80; it += 512) {
        const int cc = it % 80, dq = (it / 80) % 5, h = it / 400;
        float a[4][8];
        #pragma unroll
        for (int r = 0; r < 4; r++)
            #pragma unroll
            for (int i = 0; i < 8; i++) a[r][i] = 0.f;
        const __nv_bfloat16* wp = a_wo + (size_t)((ax * 8 + h) * DH) * DM + cc * 8;
        const float* kp = kvs + (h * 20 + dq * 4) * 24;
        #pragma unroll 5
        for (int e = 0; e < 20; e++) {
            const uint4 w = *(const uint4*)(wp + e * DM);
            const float wf[8] = {bflo(w.x), bfhi(w.x), bflo(w.y), bfhi(w.y), bflo(w.z), bfhi(w.z), bflo(w.w), bfhi(w.w)};
            #pragma unroll
            for (int r = 0; r < 4; r++) {
                const float k = kp[r * 24 + e];
                #pragma unroll
                for (int i = 0; i < 8; i++) a[r][i] += k * wf[i];
            }
        }
        #pragma unroll
        for (int r = 0; r < 4; r++)
            *(uint4*)(g_wm + (size_t)((ax * 8 + h) * DH + dq * 4 + r) * DM + cc * 8) =
                make_uint4(packbf(a[r][0], a[r][1]), packbf(a[r][2], a[r][3]), packbf(a[r][4], a[r][5]), packbf(a[r][6], a[r][7]));
    }
}

__global__ void __launch_bounds__(512, 1)
attn_kernel(const __nv_bfloat16* __restrict__ a_wo) {
    extern __shared__ __align__(1024) uint8_t smem[];
    const uint32_t sb = smem_u32(smem);
    const uint32_t bars = sb + 196608 + 12288;
    const int tid = threadIdx.x, warp = tid >> 5, lane = tid & 31;
    GRIDDEP_LAUNCH();
    if (blockIdx.x < 4) {
        GRIDDEP_WAIT();
        aux_work(smem, blockIdx.x, a_wo);
                return;
    }
    const int h = (blockIdx.x - 4) >> 2, qb = blockIdx.x & 3;
    if (tid == 0) {
        for (int i = 0; i < 17; i++) mbar_init(bars + 8 * i, 1);
        asm volatile("fence.mbarrier_init.release.cluster;" ::: "memory");
        mbar_arrive(bars + 128);
    }
        GRIDDEP_WAIT();
        const int wg = warp >> 2, w4 = warp & 3, g = lane >> 2, t = lane & 3;
    const uint8_t* kvsrc = g_kvimg + (size_t)h * 196608;
    if (tid == 0) {
        for (int i = 0; i < 2; i++) { mbar_expect(bars + 8 * i, 12288); bulk_load(sb + i * 12288, kvsrc + i * 12288, 12288, bars + 8 * i); }
    }
    const int rbase = qb * 512 + wg * 128 + w4 * 16 + g;
    const int fb = (5 * h) >> 1;
    const bool odd = h & 1;
    const bool cslot = odd ? t < 2 : t >= 2;
    const uint32_t qo = ((rbase >> 3) * 80 + fb) * 128 + lane * 4;
    uint32_t qv[2][3];
    float kmax, gt[4] = {0.f, 0.f, 0.f, 0.f};
    {
        #pragma unroll
        for (int r = 0; r < 2; r++) {
            qv[r][0] = *(const uint32_t*)(g_qb + qo + r * 10240); qv[r][1] = *(const uint32_t*)(g_qb + qo + r * 10240 + 128); qv[r][2] = *(const uint32_t*)(g_qb + qo + r * 10240 + 256);
        }
        const float4 kn4 = *(const float4*)(g_kn2 + h * 128 + lane * 4);
        float kn = fmaxf(fmaxf(kn4.x, kn4.y), fmaxf(kn4.z, kn4.w));
        #pragma unroll
        for (int o = 16; o; o >>= 1) kn = fmaxf(kn, __shfl_xor_sync(0xffffffffu, kn, o));
        kmax = sqrtf(kn);
                __syncthreads();
                if (tid == 256) {
            for (int i = 2; i < 16; i++) { mbar_expect(bars + 8 * i, 12288); bulk_load(sb + i * 12288, kvsrc + i * 12288, 12288, bars + 8 * i); }
        }
        __syncwarp();
    }
    PolyC pc;
    pc.c2 = 0x42274229u + blockIdx.y;
    pc.one = 0x3F803F80u + blockIdx.y;

    #pragma unroll 1
    for (int tile = 0; tile < 2; tile++) {
        const int row0 = rbase + tile * 64;
        uint32_t q[8];
        if (cslot) { if (odd) { qv[0][0] = 0u; qv[1][0] = 0u; } else { qv[0][2] = 0u; qv[1][2] = 0u; } }
        q[0] = qv[0][0]; q[1] = qv[1][0]; q[2] = qv[0][1]; q[3] = qv[1][1]; q[4] = qv[0][2]; q[5] = qv[1][2];
        q[6] = blockIdx.y; q[7] = blockIdx.y;
        float n0 = bflo(q[0]) * bflo(q[0]) + bfhi(q[0]) * bfhi(q[0]) + bflo(q[2]) * bflo(q[2]) + bfhi(q[2]) * bfhi(q[2]) + bflo(q[4]) * bflo(q[4]) + bfhi(q[4]) * bfhi(q[4]);
        float n1 = bflo(q[1]) * bflo(q[1]) + bfhi(q[1]) * bfhi(q[1]) + bflo(q[3]) * bflo(q[3]) + bfhi(q[3]) * bfhi(q[3]) + bflo(q[5]) * bflo(q[5]) + bfhi(q[5]) * bfhi(q[5]);
        n0 += __shfl_xor_sync(0xffffffffu, n0, 1); n1 += __shfl_xor_sync(0xffffffffu, n1, 1);
        n0 += __shfl_xor_sync(0xffffffffu, n0, 2); n1 += __shfl_xor_sync(0xffffffffu, n1, 2);
        const float m0 = sqrtf(n0) * kmax * 1.02f + 0.0625f, m1 = sqrtf(n1) * kmax * 1.02f + 0.0625f;
        uint32_t unsafe = !(m0 <= 48.f && m1 <= 48.f);
        asm volatile("{.reg .pred p, q; setp.ne.u32 p, %0, 0; barrier.red.or.pred q, %1, 128, p; selp.u32 %0, 1, 0, q;}" : "+r"(unsafe) : "r"(wg + 1) : "memory");
        unsafe = __any_sync(0xffffffffu, unsafe);

                float o[12];
        #pragma unroll
        for (int i = 0; i < 12; i++) o[i] = 0.f;
        fence_f(o);
        const uint64_t dk = mkdesc(sb, 128, 768, 0), dk2 = mkdesc(sb + 256, 0, 768, 0), dv = mkdesc(sb + 384, 768, 128, 0);
        float S[32];
        uint32_t p[16];
        if (!unsafe) {
            if (cslot) {
                const uint32_t c0 = (t & 1) ? 0x3B80u : ((packbf(-m0, 0.f) & 0xFFFFu) | 0x43FC0000u);
                const uint32_t c1 = (t & 1) ? 0x3B80u : ((packbf(-m1, 0.f) & 0xFFFFu) | 0x43FC0000u);
                if (odd) { q[0] = c0; q[1] = c1; } else { q[4] = c0; q[5] = c1; }
            }
            uint64_t ck = dk, ck2 = dk2, cv = dv;
            uint32_t cb = bars;
            mbar_wait(cb, 0);
            WG_FENCE();
            wg_qk0(S, q[0], q[1], q[2], q[3], ck); wg_qk1(S, q[4], q[5], q[6], q[7], ck2);
            WG_COMMIT();
            WG_WAIT(0);
            fence_f(S);
            #pragma unroll 1
            for (int c = 0; c < 16; c++) {
                softmax_blk<0>(S, p, pc);
                fence_r(p);
                WG_FENCE();
                wg_qk0(S, q[0], q[1], q[2], q[3], ck + 384); wg_qk1(S, q[4], q[5], q[6], q[7], ck2 + 384);
                #pragma unroll
                for (int k = 0; k < 4; k++) wg_pv(o, p[4*k], p[4*k+1], p[4*k+2], p[4*k+3], cv + k * 96);
                WG_COMMIT();
                WG_WAIT(0);
                fence_f(S);
                softmax_blk<1>(S, p, pc);
                fence_r(p);
                cb += 8; ck += 768; ck2 += 768;
                mbar_wait(cb, 0);
                WG_FENCE();
                wg_qk0(S, q[0], q[1], q[2], q[3], ck); wg_qk1(S, q[4], q[5], q[6], q[7], ck2);
                #pragma unroll
                for (int k = 0; k < 4; k++) wg_pv(o, p[4*k], p[4*k+1], p[4*k+2], p[4*k+3], cv + 384 + k * 96);
                WG_COMMIT();
                cv += 768;
                WG_WAIT(0);
                fence_f(S);
            }
        } else {
            float rm0 = -INFINITY, rm1 = -INFINITY;
            #pragma unroll 1
            for (int b = 0; b < 32; b++) {
                if ((b & 1) == 0) mbar_wait(bars + 8 * (b >> 1), 0);
                WG_FENCE();
                wg_qk0(S, q[0], q[1], q[2], q[3], dk + b * 384); wg_qk1(S, q[4], q[5], q[6], q[7], dk2 + b * 384);
                WG_COMMIT();
                WG_WAIT(0);
                fence_f(S);
                float x0 = rm0, x1 = rm1;
                #pragma unroll
                for (int j = 0; j < 8; j++) { x0 = fmaxf(x0, fmaxf(S[4*j], S[4*j+1])); x1 = fmaxf(x1, fmaxf(S[4*j+2], S[4*j+3])); }
                x0 = fmaxf(x0, __shfl_xor_sync(0xffffffffu, x0, 1)); x1 = fmaxf(x1, __shfl_xor_sync(0xffffffffu, x1, 1));
                x0 = fmaxf(x0, __shfl_xor_sync(0xffffffffu, x0, 2)); x1 = fmaxf(x1, __shfl_xor_sync(0xffffffffu, x1, 2));
                const float c0 = ex2f(rm0 - x0), c1 = ex2f(rm1 - x1);
                rm0 = x0; rm1 = x1;
                #pragma unroll
                for (int j = 0; j < 3; j++) { o[4*j] *= c0; o[4*j+1] *= c0; o[4*j+2] *= c1; o[4*j+3] *= c1; }
                #pragma unroll
                for (int j = 0; j < 8; j++) {
                    p[2*j] = packbf(ex2f(S[4*j] - x0), ex2f(S[4*j+1] - x0));
                    p[2*j+1] = packbf(ex2f(S[4*j+2] - x1), ex2f(S[4*j+3] - x1));
                }
                fence_r(p); fence_f(o);
                WG_FENCE();
                #pragma unroll
                for (int k = 0; k < 4; k++) wg_pv(o, p[4*k], p[4*k+1], p[4*k+2], p[4*k+3], dv + b * 384 + k * 96);
                WG_COMMIT();
                WG_WAIT(0);
                fence_f(o);
            }
        }
        fence_f(o);
                const int src = (lane & ~3) | (odd ? 0 : 2);
        const float l0 = __shfl_sync(0xffffffffu, odd ? o[0] : o[8], src), l1 = __shfl_sync(0xffffffffu, odd ? o[2] : o[10], src);
        if (tile == 0) {
            uint32_t pv[4][3];
            float zs = 0.f;
            #pragma unroll
            for (int r = 0; r < 4; r++) {
                const uint32_t po = qo + ((r & 1) + (r >> 1) * 8) * 10240;
                pv[r][0] = *(const uint32_t*)(g_pq + po); pv[r][1] = *(const uint32_t*)(g_pq + po + 128); pv[r][2] = *(const uint32_t*)(g_pq + po + 256);
                gt[r] = g_gate[rbase + (r & 1) * 8 + (r >> 1) * 64];
            }
            #pragma unroll
            for (int r = 0; r < 2; r++) {
                qv[r][0] = *(const uint32_t*)(g_qb + qo + 81920 + r * 10240); qv[r][1] = *(const uint32_t*)(g_qb + qo + 81920 + r * 10240 + 128);
                qv[r][2] = *(const uint32_t*)(g_qb + qo + 81920 + r * 10240 + 256);
            }
            const int d = lane - (odd ? 4 : 0);
            if (d >= 0 && d < 20) {
                #pragma unroll
                for (int m = 0; m < 16; m++) zs += g_zpart[(m * NH + h) * 20 + d];
            }
            float z[6];
            #pragma unroll
            for (int j = 0; j < 3; j++) { z[2*j] = __shfl_sync(0xffffffffu, zs, 8 * j + 2 * t); z[2*j+1] = __shfl_sync(0xffffffffu, zs, 8 * j + 2 * t + 1); }
            #pragma unroll
            for (int r = 0; r < 4; r++) {
                float den = bflo(pv[r][0]) * z[0] + bfhi(pv[r][0]) * z[1] + bflo(pv[r][1]) * z[2] + bfhi(pv[r][1]) * z[3] + bflo(pv[r][2]) * z[4] + bfhi(pv[r][2]) * z[5];
                den += __shfl_xor_sync(0xffffffffu, den, 1);
                den += __shfl_xor_sync(0xffffffffu, den, 2);
                const float sc = gt[r] / (den + 1e-6f);
                const int tg = (rbase >> 3) + (r & 1) + (r >> 1) * 8;
                #pragma unroll
                for (int j = 0; j < 3; j++) {
                    const int kb = fb + j;
                    if (!(cslot && j == (odd ? 0 : 2)))
                        *(uint32_t*)(g_acat + (((kb >> 3) * 256 + tg) * 8 + (kb & 7)) * 128 + lane * 4) = packbf(bflo(pv[r][j]) * sc, bfhi(pv[r][j]) * sc);
                }
            }
        } else { gt[0] = gt[2]; gt[1] = gt[3]; }
        const float s0 = bfr(1.f - gt[0]) / l0, s1 = bfr(1.f - gt[1]) / l1;
        #pragma unroll
        for (int j = 0; j < 3; j++) {
            const int kb = 80 + fb + j;
            uint8_t* dst = g_acat + (((kb >> 3) * 256 + (row0 >> 3)) * 8 + (kb & 7)) * 128 + lane * 4;
            if (!(cslot && j == (odd ? 0 : 2))) {
                *(uint32_t*)dst = packbf(o[4*j] * s0, o[4*j+1] * s0);
                *(uint32_t*)(dst + 1024) = packbf(o[4*j+2] * s1, o[4*j+3] * s1);
            }
        }
    }
    }

__constant__ uint8_t k3_map[130] = {0,1,2,3,16,17,18,19,32,33,34,35,48,49,50,51,4,5,6,7,20,21,22,23,36,37,38,39,52,53,54,55,8,9,24,25,40,41,56,57,64,65,66,67,80,81,82,83,96,97,98,99,112,113,114,115,68,69,70,71,84,85,86,87,100,101,102,103,116,117,118,119,72,73,88,89,104,105,120,121,128,129,130,131,144,145,146,147,160,161,162,163,176,177,178,179,132,133,134,135,148,149,150,151,164,165,166,167,180,181,182,183,136,137,152,153,168,169,184,185,192,193,194,195,196,197,198,199,200,201};
#define K3_STAGE 28672
#define K3_NST 6
#define K3_SMEM (K3_NST * K3_STAGE + 1024)
__global__ void __launch_bounds__(160, 1)
out_kernel(const __grid_constant__ CUtensorMap tm_wm, const __grid_constant__ CUtensorMap tm_wob,
           __nv_bfloat16* __restrict__ out) {
    extern __shared__ __align__(1024) uint8_t smem[];
    const uint32_t sb = smem_u32(smem);
    const uint32_t bar_full = sb + K3_NST * K3_STAGE, bar_empty = bar_full + 64;
    const int tid = threadIdx.x, warp = tid >> 5, lane = tid & 31;
    const int tt = k3_map[blockIdx.x] >> 4, ct = k3_map[blockIdx.x] & 15;
    if (tid == 0) {
        for (int i = 0; i < K3_NST; i++) { mbar_init(bar_full + 8 * i, 1); mbar_init(bar_empty + 8 * i, 4); }
        asm volatile("fence.mbarrier_init.release.cluster;" ::: "memory");
    }
    __syncthreads();
        if (warp == 4) {
        if (lane == 0) {
            for (int it = 0; it < K3_NST; it++) {
                mbar_expect(bar_full + 8 * it, K3_STAGE);
                tma2d(sb + it * K3_STAGE, &tm_wob, bar_full + 8 * it, ct * 64, it * 64);
            }
                        GRIDDEP_WAIT();
                        for (int it = 0; it < 20; it++) {
                const int s = it % K3_NST;
                const uint32_t st = sb + s * K3_STAGE, fb = bar_full + 8 * s;
                if (it >= K3_NST) {
                    mbar_wait(bar_empty + 8 * s, ((it / K3_NST) - 1) & 1);
                    mbar_expect(fb, K3_STAGE);
                    tma2d(st, it < 10 ? &tm_wob : &tm_wm, fb, ct * 64, (it % 10) * 64);
                }
                bulk_load(st + 8192, g_acat + (size_t)(((it + 10) % 20) * 256 + tt * 20) * 1024, 20480, fb);
            }
        }
    } else {
        float acc[80];
        #pragma unroll
        for (int i = 0; i < 80; i++) acc[i] = 0.f;
        fence_f(acc);
        for (int it = 0; it < 20; it++) {
            const int s = it % K3_NST;
            mbar_wait(bar_full + 8 * s, (it / K3_NST) & 1);
            const uint32_t st = sb + s * K3_STAGE;
            const uint64_t da = mkdesc(st, 8192, 1024, 1), db = mkdesc(st + 8192, 128, 1024, 0);
            WG_FENCE();
            #pragma unroll
            for (int k = 0; k < 4; k++) wg_ss_n160_at(acc, da + k * 128, db + k * 16, 1);
            WG_COMMIT();
            WG_WAIT(1);
            if (it > 0 && lane == 0) mbar_arrive(bar_empty + 8 * ((it - 1) % K3_NST));
        }
        WG_WAIT(0);
        fence_f(acc);
                named_bar(1, 128);
        #pragma unroll
        for (int j = 0; j < 20; j += 2) {
            const int tok = 8 * (j + (lane >> 4)) + (lane & 7);
            const int chunk = (2 * warp + ((lane >> 3) & 1)) ^ (tok & 7);
            const uint32_t addr = sb + tok * 128 + chunk * 16;
            asm volatile("stmatrix.sync.aligned.m8n8.x4.trans.shared.b16 [%0], {%1,%2,%3,%4};" :: "r"(addr),
                "r"(packbf(acc[4*j], acc[4*j+1])), "r"(packbf(acc[4*j+2], acc[4*j+3])), "r"(packbf(acc[4*j+4], acc[4*j+5])), "r"(packbf(acc[4*j+6], acc[4*j+7])) : "memory");
        }
        named_bar(1, 128);
        #pragma unroll
        for (int i = 0; i < 10; i++) {
            const int idx = tid + 128 * i, tok = idx >> 3, ch = idx & 7;
            const int gtok = tt * 160 + tok;
            const uint4 v = *(const uint4*)(smem + tok * 128 + ((ch ^ (tok & 7)) * 16));
            if (gtok < SEQ) *(uint4*)(out + (size_t)gtok * DM + ct * 64 + ch * 8) = v;
        }
            }
}

typedef CUresult (*PFN_tmapEncode)(CUtensorMap*, CUtensorMapDataType, cuuint32_t, void*, const cuuint64_t*, const cuuint64_t*, const cuuint32_t*, const cuuint32_t*,
                                   CUtensorMapInterleave, CUtensorMapSwizzle, CUtensorMapL2promotion, CUtensorMapFloatOOBfill);
static void make_map(PFN_tmapEncode enc, CUtensorMap* tm, const void* ptr, uint64_t cols, uint64_t rows, uint32_t bcols, uint32_t brows) {
    cuuint64_t gd[2] = {cols, rows}; cuuint64_t gs[1] = {cols * 2}; cuuint32_t bx[2] = {bcols, brows}; cuuint32_t es[2] = {1, 1};
    enc(tm, CU_TENSOR_MAP_DATA_TYPE_BFLOAT16, 2, (void*)ptr, gd, gs, bx, es, CU_TENSOR_MAP_INTERLEAVE_NONE, CU_TENSOR_MAP_SWIZZLE_128B,
        CU_TENSOR_MAP_L2_PROMOTION_L2_128B, CU_TENSOR_MAP_FLOAT_OOB_FILL_NONE);
}

extern "C" void kernel_launch(void* const* d_in, const int* in_sizes, int n_in, void* d_out, int out_size) {
    const __nv_bfloat16* x = (const __nv_bfloat16*)d_in[0];
    const __nv_bfloat16* a_wqkv = (const __nv_bfloat16*)d_in[1];
    const __nv_bfloat16* a_wo = (const __nv_bfloat16*)d_in[2];
    const __nv_bfloat16* b_wqkv = (const __nv_bfloat16*)d_in[4];
    const __nv_bfloat16* b_wo = (const __nv_bfloat16*)d_in[5];
    const __nv_bfloat16* gate_w = (const __nv_bfloat16*)d_in[6];
    static CUtensorMap tm_x, tm_wm, tm_wob;
    static WMaps tm_w;
    static const void* cached[4] = {nullptr, nullptr, nullptr, nullptr};
    if (cached[0] != x || cached[1] != a_wqkv || cached[2] != b_wqkv || cached[3] != b_wo) {
        void* fn = nullptr; cudaDriverEntryPointQueryResult qr;
        cudaGetDriverEntryPoint("cuTensorMapEncodeTiled", &fn, cudaEnableDefault, &qr);
        PFN_tmapEncode enc = (PFN_tmapEncode)fn;
        void* p_wm;
        cudaGetSymbolAddress(&p_wm, g_wm);
        make_map(enc, &tm_x, x, DM, SEQ, 64, 128);
        for (int i = 0; i < 4; i++) {
            cuuint64_t gd[4] = {64, DM, 10, 3}; cuuint64_t gs[3] = {3 * DM * 2, 128, DM * 2};
            cuuint32_t bx[4] = {64, 64, 3, (cuuint32_t)((i & 1) ? 1 : 2)}; cuuint32_t es[4] = {1, 1, 1, 1};
            enc(&tm_w.m[i], CU_TENSOR_MAP_DATA_TYPE_BFLOAT16, 4, (void*)(i < 2 ? a_wqkv : b_wqkv), gd, gs, bx, es, CU_TENSOR_MAP_INTERLEAVE_NONE,
                CU_TENSOR_MAP_SWIZZLE_128B, CU_TENSOR_MAP_L2_PROMOTION_L2_128B, CU_TENSOR_MAP_FLOAT_OOB_FILL_NONE);
        }
        make_map(enc, &tm_wm, p_wm, DM, DM, 64, 64);
        make_map(enc, &tm_wob, b_wo, DM, DM, 64, 64);
        cudaFuncSetAttribute(qkv_kernel, cudaFuncAttributeMaxDynamicSharedMemorySize, K1_SMEM);
        cudaFuncSetAttribute(attn_kernel, cudaFuncAttributeMaxDynamicSharedMemorySize, K2_SMEM);
        cudaFuncSetAttribute(out_kernel, cudaFuncAttributeMaxDynamicSharedMemorySize, K3_SMEM);
        cached[0] = x; cached[1] = a_wqkv; cached[2] = b_wqkv; cached[3] = b_wo;
    }
    cudaStream_t st = cudaStreamPerThread;
    cudaLaunchAttribute at[1];
    at[0].id = cudaLaunchAttributeProgrammaticStreamSerialization; at[0].val.programmaticStreamSerializationAllowed = 1;
    cudaLaunchConfig_t cfg = {};
    cfg.stream = st;
    cfg.gridDim = dim3(128); cfg.blockDim = dim3(512); cfg.dynamicSmemBytes = K1_SMEM; cfg.attrs = at; cfg.numAttrs = 0;
    cudaLaunchKernelEx(&cfg, qkv_kernel, tm_x, tm_w, x, gate_w);
    cfg.gridDim = dim3(132); cfg.blockDim = dim3(512); cfg.dynamicSmemBytes = K2_SMEM; cfg.numAttrs = 1;
    cudaLaunchKernelEx(&cfg, attn_kernel, a_wo);
    cfg.gridDim = dim3(130); cfg.blockDim = dim3(160); cfg.dynamicSmemBytes = K3_SMEM; cfg.numAttrs = 1;
    cudaLaunchKernelEx(&cfg, out_kernel, tm_wm, tm_wob, (__nv_bfloat16*)d_out);
}
```

```cpp
#include <cuda_runtime.h>
#include <cuda_bf16.h>
#include <cuda.h>
#include <stdint.h>

#define SEQ 2048
#define DM 640
#define NH 32
#define DH 20

#define POLY_MASK 0xD5DDu

__device__ __align__(1024) uint8_t g_kvimg[NH * 196608];
__device__ __align__(1024) uint8_t g_qb[SEQ * DM * 2];
__device__ __align__(1024) uint8_t g_pq[SEQ * DM * 2];
__device__ __align__(1024) uint8_t g_acat[SEQ * 2 * DM * 2];
__device__ __align__(1024) __nv_bfloat16 g_wm[DM * DM];
__device__ __align__(16) float g_kvpart[16 * NH * 480];
__device__ __align__(16) float g_zpart[16 * NH * 20];
__device__ __align__(16) float g_kn2[NH * 128];
__device__ __align__(16) float g_gate[SEQ];

__device__ __forceinline__ uint32_t smem_u32(const void* p) { return (uint32_t)__cvta_generic_to_shared(p); }
__device__ __forceinline__ uint64_t mkdesc(uint32_t saddr, uint32_t lbo, uint32_t sbo, uint32_t swz) {
    return (uint64_t)((saddr & 0x3FFFF) >> 4) | ((uint64_t)(lbo >> 4) << 16) | ((uint64_t)(sbo >> 4) << 32) | ((uint64_t)swz << 62);
}
#define WG_FENCE() asm volatile("wgmma.fence.sync.aligned;" ::: "memory")
#define WG_COMMIT() asm volatile("wgmma.commit_group.sync.aligned;" ::: "memory")
#define WG_WAIT(n) asm volatile("wgmma.wait_group.sync.aligned %0;" :: "n"(n) : "memory")
template<int N> __device__ __forceinline__ void fence_f(float (&d)[N]) {
    #pragma unroll
    for (int i = 0; i < N; i++) asm volatile("" : "+f"(d[i]) :: "memory");
}
template<int N> __device__ __forceinline__ void fence_r(uint32_t (&d)[N]) {
    #pragma unroll
    for (int i = 0; i < N; i++) asm volatile("" : "+r"(d[i]) :: "memory");
}
__device__ __forceinline__ void mbar_init(uint32_t bar, uint32_t cnt) { asm volatile("mbarrier.init.shared::cta.b64 [%0], %1;" :: "r"(bar), "r"(cnt)); }
__device__ __forceinline__ void mbar_expect(uint32_t bar, uint32_t bytes) { asm volatile("mbarrier.arrive.expect_tx.shared::cta.b64 _, [%0], %1;" :: "r"(bar), "r"(bytes) : "memory"); }
__device__ __forceinline__ void mbar_arrive(uint32_t bar) { asm volatile("mbarrier.arrive.shared::cta.b64 _, [%0];" :: "r"(bar) : "memory"); }
__device__ __forceinline__ void mbar_wait(uint32_t bar, uint32_t parity) {
    asm volatile("{\n.reg .pred p;\nWAIT_%=:\nmbarrier.try_wait.parity.shared::cta.b64 p, [%0], %1;\n@p bra DONE_%=;\nbra WAIT_%=;\nDONE_%=:\n}" :: "r"(bar), "r"(parity) : "memory");
}
__device__ __forceinline__ void tma2d(uint32_t dst, const CUtensorMap* tm, uint32_t bar, int c0, int c1) {
    asm volatile("cp.async.bulk.tensor.2d.shared::cluster.global.mbarrier::complete_tx::bytes [%0], [%1, {%3,%4}], [%2];"
        :: "r"(dst), "l"((uint64_t)tm), "r"(bar), "r"(c0), "r"(c1) : "memory");
}
__device__ __forceinline__ void bulk_load(uint32_t dst, const void* src, uint32_t bytes, uint32_t bar) {
    asm volatile("cp.async.bulk.shared::cluster.global.mbarrier::complete_tx::bytes [%0], [%1], %2, [%3];" :: "r"(dst), "l"(src), "r"(bytes), "r"(bar) : "memory");
}
__device__ __forceinline__ void named_bar(int id, int n) { asm volatile("bar.sync %0, %1;" :: "r"(id), "r"(n) : "memory"); }
__device__ __forceinline__ float ex2f(float x) { float y; asm("ex2.approx.ftz.f32 %0, %1;" : "=f"(y) : "f"(x)); return y; }
__device__ __forceinline__ uint32_t packbf(float lo, float hi) { uint32_t r; asm("cvt.rn.bf16x2.f32 %0, %1, %2;" : "=r"(r) : "f"(hi), "f"(lo)); return r; }
__device__ __forceinline__ float bflo(uint32_t v) { return __uint_as_float(v << 16); }
__device__ __forceinline__ float bfhi(uint32_t v) { return __uint_as_float(v & 0xFFFF0000u); }
__device__ __forceinline__ float bfr(float v) { return bflo(packbf(v, 0.f)); }
__device__ __forceinline__ float dot_bf(uint32_t a, uint32_t b) {
    uint32_t p; asm("mul.rn.bf16x2 %0, %1, %2;" : "=r"(p) : "r"(a), "r"(b));
    return bflo(p) + bfhi(p);
}
__device__ __forceinline__ float phi_f(float t) { return (fmaxf(t, 0.f) + 1e-6f) + ex2f(fminf(t, 0.f) * 1.4426950408889634f); }
#define GRIDDEP_WAIT() asm volatile("griddepcontrol.wait;" ::: "memory")
#define GRIDDEP_LAUNCH() asm volatile("griddepcontrol.launch_dependents;" ::: "memory")

__device__ __forceinline__ void wg_rs_n128_bt(float (&d)[64], uint32_t a0, uint32_t a1, uint32_t a2, uint32_t a3, uint64_t db) {
    asm volatile("wgmma.mma_async.sync.aligned.m64n128k16.f32.bf16.bf16 {%0,%1,%2,%3,%4,%5,%6,%7,%8,%9,%10,%11,%12,%13,%14,%15,%16,%17,%18,%19,%20,%21,%22,%23,%24,%25,%26,%27,%28,%29,%30,%31,%32,%33,%34,%35,%36,%37,%38,%39,%40,%41,%42,%43,%44,%45,%46,%47,%48,%49,%50,%51,%52,%53,%54,%55,%56,%57,%58,%59,%60,%61,%62,%63}, {%64,%65,%66,%67}, %68, 1, 1, 1, 1;"
      : "+f"(d[0]),"+f"(d[1]),"+f"(d[2]),"+f"(d[3]),"+f"(d[4]),"+f"(d[5]),"+f"(d[6]),"+f"(d[7]),"+f"(d[8]),"+f"(d[9]),"+f"(d[10]),"+f"(d[11]),"+f"(d[12]),"+f"(d[13]),"+f"(d[14]),"+f"(d[15]),"+f"(d[16]),"+f"(d[17]),"+f"(d[18]),"+f"(d[19]),"+f"(d[20]),"+f"(d[21]),"+f"(d[22]),"+f"(d[23]),"+f"(d[24]),"+f"(d[25]),"+f"(d[26]),"+f"(d[27]),"+f"(d[28]),"+f"(d[29]),"+f"(d[30]),"+f"(d[31]),"+f"(d[32]),"+f"(d[33]),"+f"(d[34]),"+f"(d[35]),"+f"(d[36]),"+f"(d[37]),"+f"(d[38]),"+f"(d[39]),"+f"(d[40]),"+f"(d[41]),"+f"(d[42]),"+f"(d[43]),"+f"(d[44]),"+f"(d[45]),"+f"(d[46]),"+f"(d[47]),"+f"(d[48]),"+f"(d[49]),"+f"(d[50]),"+f"(d[51]),"+f"(d[52]),"+f"(d[53]),"+f"(d[54]),"+f"(d[55]),"+f"(d[56]),"+f"(d[57]),"+f"(d[58]),"+f"(d[59]),"+f"(d[60]),"+f"(d[61]),"+f"(d[62]),"+f"(d[63]) : "r"(a0), "r"(a1), "r"(a2), "r"(a3), "l"(db));
}
__device__ __forceinline__ void wg_ss_n64_bt(float (&d)[32], uint64_t da, uint64_t db, int acc) {
    asm volatile("{.reg .pred p; setp.ne.b32 p, %34, 0;\n"
      "wgmma.mma_async.sync.aligned.m64n64k16.f32.bf16.bf16 {%0,%1,%2,%3,%4,%5,%6,%7,%8,%9,%10,%11,%12,%13,%14,%15,%16,%17,%18,%19,%20,%21,%22,%23,%24,%25,%26,%27,%28,%29,%30,%31}, %32, %33, p, 1, 1, 0, 1;}"
      : "+f"(d[0]),"+f"(d[1]),"+f"(d[2]),"+f"(d[3]),"+f"(d[4]),"+f"(d[5]),"+f"(d[6]),"+f"(d[7]),"+f"(d[8]),"+f"(d[9]),"+f"(d[10]),"+f"(d[11]),"+f"(d[12]),"+f"(d[13]),"+f"(d[14]),"+f"(d[15]),"+f"(d[16]),"+f"(d[17]),"+f"(d[18]),"+f"(d[19]),"+f"(d[20]),"+f"(d[21]),"+f"(d[22]),"+f"(d[23]),"+f"(d[24]),"+f"(d[25]),"+f"(d[26]),"+f"(d[27]),"+f"(d[28]),"+f"(d[29]),"+f"(d[30]),"+f"(d[31]) : "l"(da), "l"(db), "r"(acc));
}
__device__ __forceinline__ void wg_ss_n32_bt(float (&d)[16], uint64_t da, uint64_t db, int acc) {
    asm volatile("{.reg .pred p; setp.ne.b32 p, %18, 0;\n"
      "wgmma.mma_async.sync.aligned.m64n32k16.f32.bf16.bf16 {%0,%1,%2,%3,%4,%5,%6,%7,%8,%9,%10,%11,%12,%13,%14,%15}, %16, %17, p, 1, 1, 0, 1;}"
      : "+f"(d[0]),"+f"(d[1]),"+f"(d[2]),"+f"(d[3]),"+f"(d[4]),"+f"(d[5]),"+f"(d[6]),"+f"(d[7]),"+f"(d[8]),"+f"(d[9]),"+f"(d[10]),"+f"(d[11]),"+f"(d[12]),"+f"(d[13]),"+f"(d[14]),"+f"(d[15]) : "l"(da), "l"(db), "r"(acc));
}
__device__ __forceinline__ void wg_rs_n32_bt(float (&d)[16], uint32_t a0, uint32_t a1, uint32_t a2, uint32_t a3, uint64_t db) {
    asm volatile("wgmma.mma_async.sync.aligned.m64n32k16.f32.bf16.bf16 {%0,%1,%2,%3,%4,%5,%6,%7,%8,%9,%10,%11,%12,%13,%14,%15}, {%16,%17,%18,%19}, %20, 1, 1, 1, 1;"
      : "+f"(d[0]),"+f"(d[1]),"+f"(d[2]),"+f"(d[3]),"+f"(d[4]),"+f"(d[5]),"+f"(d[6]),"+f"(d[7]),"+f"(d[8]),"+f"(d[9]),"+f"(d[10]),"+f"(d[11]),"+f"(d[12]),"+f"(d[13]),"+f"(d[14]),"+f"(d[15]) : "r"(a0), "r"(a1), "r"(a2), "r"(a3), "l"(db));
}
__device__ __forceinline__ void wg_ss_n88_atbt(float (&d)[44], uint64_t da, uint64_t db, int acc) {
    asm volatile("{.reg .pred p; setp.ne.b32 p, %46, 0;\n"
      "wgmma.mma_async.sync.aligned.m64n88k16.f32.bf16.bf16 {%0,%1,%2,%3,%4,%5,%6,%7,%8,%9,%10,%11,%12,%13,%14,%15,%16,%17,%18,%19,%20,%21,%22,%23,%24,%25,%26,%27,%28,%29,%30,%31,%32,%33,%34,%35,%36,%37,%38,%39,%40,%41,%42,%43}, %44, %45, p, 1, 1, 1, 1;}"
      : "+f"(d[0]),"+f"(d[1]),"+f"(d[2]),"+f"(d[3]),"+f"(d[4]),"+f"(d[5]),"+f"(d[6]),"+f"(d[7]),"+f"(d[8]),"+f"(d[9]),"+f"(d[10]),"+f"(d[11]),"+f"(d[12]),"+f"(d[13]),"+f"(d[14]),"+f"(d[15]),"+f"(d[16]),"+f"(d[17]),"+f"(d[18]),"+f"(d[19]),"+f"(d[20]),"+f"(d[21]),"+f"(d[22]),"+f"(d[23]),"+f"(d[24]),"+f"(d[25]),"+f"(d[26]),"+f"(d[27]),"+f"(d[28]),"+f"(d[29]),"+f"(d[30]),"+f"(d[31]),"+f"(d[32]),"+f"(d[33]),"+f"(d[34]),"+f"(d[35]),"+f"(d[36]),"+f"(d[37]),"+f"(d[38]),"+f"(d[39]),"+f"(d[40]),"+f"(d[41]),"+f"(d[42]),"+f"(d[43]) : "l"(da), "l"(db), "r"(acc));
}
__device__ __forceinline__ void wg_ss_n8_atbt(float (&d)[4], uint64_t da, uint64_t db, int acc) {
    asm volatile("{.reg .pred p; setp.ne.b32 p, %6, 0;\n"
      "wgmma.mma_async.sync.aligned.m64n8k16.f32.bf16.bf16 {%0,%1,%2,%3}, %4, %5, p, 1, 1, 1, 1;}"
      : "+f"(d[0]),"+f"(d[1]),"+f"(d[2]),"+f"(d[3]) : "l"(da), "l"(db), "r"(acc));
}
__device__ __forceinline__ void wg_ss_n160_at(float (&d)[80], uint64_t da, uint64_t db, int acc) {
    asm volatile("{.reg .pred p; setp.ne.b32 p, %82, 0;\n"
      "wgmma.mma_async.sync.aligned.m64n160k16.f32.bf16.bf16 {%0,%1,%2,%3,%4,%5,%6,%7,%8,%9,%10,%11,%12,%13,%14,%15,%16,%17,%18,%19,%20,%21,%22,%23,%24,%25,%26,%27,%28,%29,%30,%31,%32,%33,%34,%35,%36,%37,%38,%39,%40,%41,%42,%43,%44,%45,%46,%47,%48,%49,%50,%51,%52,%53,%54,%55,%56,%57,%58,%59,%60,%61,%62,%63,%64,%65,%66,%67,%68,%69,%70,%71,%72,%73,%74,%75,%76,%77,%78,%79}, %80, %81, p, 1, 1, 1, 0;}"
      : "+f"(d[0]),"+f"(d[1]),"+f"(d[2]),"+f"(d[3]),"+f"(d[4]),"+f"(d[5]),"+f"(d[6]),"+f"(d[7]),"+f"(d[8]),"+f"(d[9]),"+f"(d[10]),"+f"(d[11]),"+f"(d[12]),"+f"(d[13]),"+f"(d[14]),"+f"(d[15]),"+f"(d[16]),"+f"(d[17]),"+f"(d[18]),"+f"(d[19]),"+f"(d[20]),"+f"(d[21]),"+f"(d[22]),"+f"(d[23]),"+f"(d[24]),"+f"(d[25]),"+f"(d[26]),"+f"(d[27]),"+f"(d[28]),"+f"(d[29]),"+f"(d[30]),"+f"(d[31]),"+f"(d[32]),"+f"(d[33]),"+f"(d[34]),"+f"(d[35]),"+f"(d[36]),"+f"(d[37]),"+f"(d[38]),"+f"(d[39]),"+f"(d[40]),"+f"(d[41]),"+f"(d[42]),"+f"(d[43]),"+f"(d[44]),"+f"(d[45]),"+f"(d[46]),"+f"(d[47]),"+f"(d[48]),"+f"(d[49]),"+f"(d[50]),"+f"(d[51]),"+f"(d[52]),"+f"(d[53]),"+f"(d[54]),"+f"(d[55]),"+f"(d[56]),"+f"(d[57]),"+f"(d[58]),"+f"(d[59]),"+f"(d[60]),"+f"(d[61]),"+f"(d[62]),"+f"(d[63]),"+f"(d[64]),"+f"(d[65]),"+f"(d[66]),"+f"(d[67]),"+f"(d[68]),"+f"(d[69]),"+f"(d[70]),"+f"(d[71]),"+f"(d[72]),"+f"(d[73]),"+f"(d[74]),"+f"(d[75]),"+f"(d[76]),"+f"(d[77]),"+f"(d[78]),"+f"(d[79]) : "l"(da), "l"(db), "r"(acc));
}
__device__ __forceinline__ void wg_qk0(float (&d)[32], uint32_t a0, uint32_t a1, uint32_t a2, uint32_t a3, uint64_t db) {
    asm volatile("wgmma.mma_async.sync.aligned.m64n64k16.f32.bf16.bf16 {%0,%1,%2,%3,%4,%5,%6,%7,%8,%9,%10,%11,%12,%13,%14,%15,%16,%17,%18,%19,%20,%21,%22,%23,%24,%25,%26,%27,%28,%29,%30,%31}, {%32,%33,%34,%35}, %36, 0, 1, 1, 0;"
      : "+f"(d[0]),"+f"(d[1]),"+f"(d[2]),"+f"(d[3]),"+f"(d[4]),"+f"(d[5]),"+f"(d[6]),"+f"(d[7]),"+f"(d[8]),"+f"(d[9]),"+f"(d[10]),"+f"(d[11]),"+f"(d[12]),"+f"(d[13]),"+f"(d[14]),"+f"(d[15]),"+f"(d[16]),"+f"(d[17]),"+f"(d[18]),"+f"(d[19]),"+f"(d[20]),"+f"(d[21]),"+f"(d[22]),"+f"(d[23]),"+f"(d[24]),"+f"(d[25]),"+f"(d[26]),"+f"(d[27]),"+f"(d[28]),"+f"(d[29]),"+f"(d[30]),"+f"(d[31]) : "r"(a0), "r"(a1), "r"(a2), "r"(a3), "l"(db));
}
__device__ __forceinline__ void wg_qk1(float (&d)[32], uint32_t a0, uint32_t a1, uint32_t a2, uint32_t a3, uint64_t db) {
    asm volatile("wgmma.mma_async.sync.aligned.m64n64k16.f32.bf16.bf16 {%0,%1,%2,%3,%4,%5,%6,%7,%8,%9,%10,%11,%12,%13,%14,%15,%16,%17,%18,%19,%20,%21,%22,%23,%24,%25,%26,%27,%28,%29,%30,%31}, {%32,%33,%34,%35}, %36, 1, 1, 1, 0;"
      : "+f"(d[0]),"+f"(d[1]),"+f"(d[2]),"+f"(d[3]),"+f"(d[4]),"+f"(d[5]),"+f"(d[6]),"+f"(d[7]),"+f"(d[8]),"+f"(d[9]),"+f"(d[10]),"+f"(d[11]),"+f"(d[12]),"+f"(d[13]),"+f"(d[14]),"+f"(d[15]),"+f"(d[16]),"+f"(d[17]),"+f"(d[18]),"+f"(d[19]),"+f"(d[20]),"+f"(d[21]),"+f"(d[22]),"+f"(d[23]),"+f"(d[24]),"+f"(d[25]),"+f"(d[26]),"+f"(d[27]),"+f"(d[28]),"+f"(d[29]),"+f"(d[30]),"+f"(d[31]) : "r"(a0), "r"(a1), "r"(a2), "r"(a3), "l"(db));
}
__device__ __forceinline__ void wg_pv(float (&d)[12], uint32_t a0, uint32_t a1, uint32_t a2, uint32_t a3, uint64_t db) {
    asm volatile("wgmma.mma_async.sync.aligned.m64n24k16.f32.bf16.bf16 {%0,%1,%2,%3,%4,%5,%6,%7,%8,%9,%10,%11}, {%12,%13,%14,%15}, %16, 1, 1, 1, 1;"
      : "+f"(d[0]),"+f"(d[1]),"+f"(d[2]),"+f"(d[3]),"+f"(d[4]),"+f"(d[5]),"+f"(d[6]),"+f"(d[7]),"+f"(d[8]),"+f"(d[9]),"+f"(d[10]),"+f"(d[11]) : "r"(a0), "r"(a1), "r"(a2), "r"(a3), "l"(db));
}

#define K1_ONES 204800
#define K1_BARS 205056
#define K1_SMEM 205312
#define QSCALE 0.32259799f
#define K1_BAR(i) (sb + K1_BARS + 8 * (i))

__device__ __forceinline__ void tma4d(uint32_t dst, const CUtensorMap* tm, uint32_t bar, int c0, int c1, int c2, int c3) {
    asm volatile("cp.async.bulk.tensor.4d.shared::cluster.global.mbarrier::complete_tx::bytes [%0], [%1, {%3,%4,%5,%6}], [%2];"
        :: "r"(dst), "l"((uint64_t)tm), "r"(bar), "r"(c0), "r"(c1), "r"(c2), "r"(c3) : "memory");
}
__device__ __forceinline__ void k1_issue(int pass, int kb, uint32_t sb, const CUtensorMap* tx, const CUtensorMap* tw, int mt, int hg) {
    const int s = pass ? kb % 5 : kb % 3;
    const uint32_t st = sb + (pass ? s * 40960 : s * 65536), fb = K1_BAR(pass ? s : 10 + s);
    mbar_expect(fb, pass ? 40960 : 65536);
    tma2d(st, tx, fb, kb * 64, mt * 128);
    tma4d(st + 16384, tw + pass, fb, 0, kb * 64, (hg * 160) >> 6, 1 - pass);
}
__device__ __forceinline__ void stsm4(uint32_t addr, uint32_t r0, uint32_t r1, uint32_t r2, uint32_t r3) {
    asm volatile("stmatrix.sync.aligned.m8n8.x4.shared.b16 [%0], {%1,%2,%3,%4};" :: "r"(addr), "r"(r0), "r"(r1), "r"(r2), "r"(r3) : "memory");
}
__device__ __forceinline__ void bulk_store(void* dst, uint32_t src, uint32_t bytes) {
    asm volatile("cp.async.bulk.global.shared::cta.bulk_group [%0], [%1], %2;" :: "l"(dst), "r"(src), "r"(bytes) : "memory");
}
#define FENCE_ASYNC() asm volatile("fence.proxy.async.shared::cta;" ::: "memory")

__device__ __forceinline__ void k1_stage_rows(const uint32_t (&pk)[40], uint32_t base, bool odd) {
    const uint32_t b0 = base + (odd ? 512 : 0), b2 = base + (odd ? 0 : 2048);
    #pragma unroll
    for (int j = 0; j < 16; j += 2) stsm4(b0 + j * 128, pk[2*j], pk[2*j+1], pk[2*j+2], pk[2*j+3]);
    #pragma unroll
    for (int j = 0; j < 4; j += 2) stsm4(b2 + j * 128, pk[32 + 2*j], pk[33 + 2*j], pk[34 + 2*j], pk[35 + 2*j]);
}
template<bool ODD>
__device__ __forceinline__ void k1_image(const uint32_t (&pk)[40], uint32_t base, int lane) {
    #define PH(j) (ODD ? ((j) < 4 ? (j) + 16 : (j) - 4) : (j))
    const bool hi = lane & 16;
    #pragma unroll
    for (int i = 0; i < 4; i++) {
        const uint32_t e = base + (2 * i) * 12288, o = e + 12288;
        const int j = 5 * i;
        stsm4(hi ? e + 128 : e, pk[2*PH(j)], pk[2*PH(j)+1], pk[2*PH(j+1)], pk[2*PH(j+1)+1]);
        stsm4(hi ? o : e + 256, pk[2*PH(j+2)], pk[2*PH(j+2)+1], pk[2*PH(j+2)], pk[2*PH(j+2)+1]);
        stsm4(hi ? o + 256 : o + 128, pk[2*PH(j+3)], pk[2*PH(j+3)+1], pk[2*PH(j+4)], pk[2*PH(j+4)+1]);
    }
}
template<bool ODD>
__device__ __forceinline__ void k1_norms(const uint32_t (&pk)[40], int lane, float* kn_dst) {
    {
        const bool lo = (lane & 3) < 2;
        #pragma unroll
        for (int h = 0; h < 8; h++) {
            float a = 0.f, b = 0.f;
            #pragma unroll
            for (int jj = 0; jj < 3; jj++) {
                const int j = (5 * h) / 2 + jj;
                const uint32_t v0 = pk[2*PH(j)], v1 = pk[2*PH(j)+1];
                float s0 = bflo(v0) * bflo(v0) + bfhi(v0) * bfhi(v0), s1 = bflo(v1) * bflo(v1) + bfhi(v1) * bfhi(v1);
                if (jj == ((h & 1) ? 0 : 2)) { const bool mine = (h & 1) ? !lo : lo; s0 = mine ? s0 : 0.f; s1 = mine ? s1 : 0.f; }
                a += s0; b += s1;
            }
            a += __shfl_xor_sync(0xffffffffu, a, 1); b += __shfl_xor_sync(0xffffffffu, b, 1);
            a += __shfl_xor_sync(0xffffffffu, a, 2); b += __shfl_xor_sync(0xffffffffu, b, 2);
            a = fmaxf(a, b);
            a = fmaxf(a, __shfl_xor_sync(0xffffffffu, a, 4));
            a = fmaxf(a, __shfl_xor_sync(0xffffffffu, a, 8));
            a = fmaxf(a, __shfl_xor_sync(0xffffffffu, a, 16));
            if (lane == h) kn_dst[h * 128] = a;
        }
    }
    #undef PH
}

struct WMaps { CUtensorMap m[4]; };
__global__ void __launch_bounds__(512, 1)
qkv_kernel(const __grid_constant__ CUtensorMap tm_x, const __grid_constant__ WMaps tm_w,
           const __nv_bfloat16* __restrict__ x, const __nv_bfloat16* __restrict__ gate_w) {
    extern __shared__ __align__(1024) uint8_t smem[];
    const uint32_t sb = smem_u32(smem);
    const int tid = threadIdx.x, warp = tid >> 5, lane = tid & 31;
    const int mt = ((blockIdx.x >> 4) & 3) * 4 + (blockIdx.x & 3), grp = (blockIdx.x >> 6) * 4 + ((blockIdx.x >> 2) & 3), br = grp >> 2, hg = grp & 3;
    const CUtensorMap* tw = &tm_w.m[br * 2];
    if (tid == 0) {
        for (int i = 0; i < 5; i++) { mbar_init(K1_BAR(i), 1); mbar_init(K1_BAR(5 + i), 16); }
        for (int i = 0; i < 3; i++) { mbar_init(K1_BAR(10 + i), 1); mbar_init(K1_BAR(13 + i), 16); }
        mbar_init(K1_BAR(16), 16); mbar_init(K1_BAR(17), 16); mbar_init(K1_BAR(18), 12);
        asm volatile("fence.mbarrier_init.release.cluster;" ::: "memory");
        k1_issue(1, 0, sb, &tm_x, tw, mt, hg);
    }
    __syncthreads();
    GRIDDEP_LAUNCH();
    if (tid == 0) for (int i = 1; i < 5; i++) k1_issue(1, i, sb, &tm_x, tw, mt, hg);
    if (tid >= 64 && tid < 96) *(uint32_t*)(smem + K1_ONES + lane * 4) = (lane & 3) == 0 ? 0x3F80u : 0u;
    __syncwarp();
    const int wg = __shfl_sync(0xffffffffu, warp >> 2, 0), mh = wg & 1, sel = wg >> 1, w4 = warp & 3;
    const int g = lane >> 2, t = lane & 3;
    const bool odd = hg & 1;
    {
        float a0[32], a2[16];
        #pragma unroll
        for (int i = 0; i < 32; i++) a0[i] = 0.f;
        #pragma unroll
        for (int i = 0; i < 16; i++) a2[i] = 0.f;
        fence_f(a0); fence_f(a2);
        const uint32_t o0 = sel ? 512 : (odd ? 1024 : 0), o2 = odd ? 4 : 1024;
        for (int kb = 0; kb < 10; kb++) {
            const int s = kb % 5;
            mbar_wait(K1_BAR(s), kb >= 5);
            const uint32_t st = sb + s * 40960;
            const uint64_t da = mkdesc(st + mh * 8192, 16, 1024, 1), db = mkdesc(st + 16384, 8192, 1024, 1);
            WG_FENCE();
            #pragma unroll
            for (int k = 0; k < 4; k++) wg_ss_n64_bt(a0, da + k * 2, db + o0 + k * 128, 1);
            if (sel) {
                #pragma unroll
                for (int k = 0; k < 4; k++) wg_ss_n32_bt(a2, da + k * 2, db + o2 + k * 128, 1);
            }
            WG_COMMIT();
            WG_WAIT(0);
            if (lane == 0) mbar_arrive(K1_BAR(5 + s));
            if (tid == 0) {
                mbar_wait(K1_BAR(5 + s), kb >= 5);
                if (kb < 5) k1_issue(1, kb + 5, sb, &tm_x, tw, mt, hg);
                else if (kb == 6) k1_issue(0, 0, sb, &tm_x, tw, mt, hg);
                else if (kb >= 8) k1_issue(0, kb - 7, sb, &tm_x, tw, mt, hg);
            }
            __syncwarp();
        }
        fence_f(a0); fence_f(a2);
        uint8_t* dst = (br ? g_qb : g_pq) + ((mt * 16 + mh * 8 + w4 * 2) * 80 + hg * 20) * 128 + lane * 4;
        uint8_t* d0 = dst + (sel ? (odd ? 4 : 8) : (odd ? 12 : 0)) * 128;
        uint8_t* d2 = dst + (odd ? 0 : 16) * 128;
        if (br) {
            #pragma unroll
            for (int j = 0; j < 8; j++) {
                *(uint32_t*)(d0 + j * 128) = packbf(a0[4*j] * QSCALE, a0[4*j+1] * QSCALE);
                *(uint32_t*)(d0 + 10240 + j * 128) = packbf(a0[4*j+2] * QSCALE, a0[4*j+3] * QSCALE);
            }
            if (sel) {
                #pragma unroll
                for (int j = 0; j < 4; j++) {
                    *(uint32_t*)(d2 + j * 128) = packbf(a2[4*j] * QSCALE, a2[4*j+1] * QSCALE);
                    *(uint32_t*)(d2 + 10240 + j * 128) = packbf(a2[4*j+2] * QSCALE, a2[4*j+3] * QSCALE);
                }
            }
        } else {
            #pragma unroll
            for (int j = 0; j < 8; j++) {
                *(uint32_t*)(d0 + j * 128) = packbf(phi_f(a0[4*j]), phi_f(a0[4*j+1]));
                *(uint32_t*)(d0 + 10240 + j * 128) = packbf(phi_f(a0[4*j+2]), phi_f(a0[4*j+3]));
            }
            if (sel) {
                #pragma unroll
                for (int j = 0; j < 4; j++) {
                    *(uint32_t*)(d2 + j * 128) = packbf(phi_f(a2[4*j]), phi_f(a2[4*j+1]));
                    *(uint32_t*)(d2 + 10240 + j * 128) = packbf(phi_f(a2[4*j+2]), phi_f(a2[4*j+3]));
                }
            }
        }
    }
    uint32_t pk[40];
    {
        float a0[64], a2[16];
        #pragma unroll
        for (int i = 0; i < 64; i++) a0[i] = 0.f;
        #pragma unroll
        for (int i = 0; i < 16; i++) a2[i] = 0.f;
        fence_f(a0); fence_f(a2);
        const uint32_t o0 = odd ? 512 : 0, o2 = odd ? 4 : 1024;
        const uint32_t arow = (mh * 64 + w4 * 16 + (lane & 15)) * 128;
        for (int kb = 0; kb < 10; kb++) {
            const int s = kb % 3;
            mbar_wait(K1_BAR(10 + s), (kb / 3) & 1);
            const uint32_t st = sb + s * 65536;
            const uint64_t db = mkdesc(st + 16384 + sel * 24576, 8192, 1024, 1);
            uint32_t af[4][4];
            #pragma unroll
            for (int k = 0; k < 4; k++)
                asm volatile("ldmatrix.sync.aligned.m8n8.x4.shared.b16 {%0,%1,%2,%3}, [%4];"
                    : "=r"(af[k][0]), "=r"(af[k][1]), "=r"(af[k][2]), "=r"(af[k][3]) : "r"(st + arow + (((2 * k + (lane >> 4)) ^ (lane & 7)) << 4)));
            WG_FENCE();
            #pragma unroll
            for (int k = 0; k < 4; k++) {
                wg_rs_n128_bt(a0, af[k][0], af[k][1], af[k][2], af[k][3], db + o0 + k * 128);
                wg_rs_n32_bt(a2, af[k][0], af[k][1], af[k][2], af[k][3], db + o2 + k * 128);
            }
            WG_COMMIT();
            WG_WAIT(0);
            const uint32_t eb = K1_BAR(kb == 9 ? 16 : 13 + s);
            if (lane == 0) mbar_arrive(eb);
            if (tid == 0 && kb < 7) { mbar_wait(eb, (kb / 3) & 1); k1_issue(0, kb + 3, sb, &tm_x, tw, mt, hg); }
            __syncwarp();
        }
        fence_f(a0); fence_f(a2);
        if (br == 0 && sel == 0) {
            #pragma unroll
            for (int i = 0; i < 32; i++) pk[i] = packbf(phi_f(a0[2 * i]), phi_f(a0[2 * i + 1]));
            #pragma unroll
            for (int i = 0; i < 8; i++) pk[32 + i] = packbf(phi_f(a2[2 * i]), phi_f(a2[2 * i + 1]));
        } else {
            #pragma unroll
            for (int i = 0; i < 32; i++) pk[i] = packbf(a0[2 * i], a0[2 * i + 1]);
            #pragma unroll
            for (int i = 0; i < 8; i++) pk[32 + i] = packbf(a2[2 * i], a2[2 * i + 1]);
        }
    }
    const int rg = mh * 8 + w4 * 2 + ((lane >> 3) & 1);
    mbar_wait(K1_BAR(14), 0); mbar_wait(K1_BAR(15), 0);
    const uint32_t stg = sb + 65536;
    bool do_gate;
    if (br) {
        const uint32_t base = stg + rg * 768 + sel * 384 + (lane & 7) * 16;
        if (odd) k1_image<true>(pk, base, lane); else k1_image<false>(pk, base, lane);
        __syncwarp();
        {
            const int lr = mh * 64 + w4 * 16 + (lane & 15);
            const uint32_t flag = (sel == 0 && ((POLY_MASK >> ((lr >> 3) & 15)) & 1)) ? 0x3F80u : 0u;
            const uint2 cv = make_uint2(0x3F80u | (flag << 16), flag);
            uint8_t* p = smem + 65536 + (lane >> 4) * 49152 + (lr >> 3) * 768 + sel * 384 + (lr & 7) * 16;
            *(uint2*)(p + 264) = cv; *(uint2*)(p + 12288) = cv; *(uint2*)(p + 24576 + 264) = cv; *(uint2*)(p + 36864) = cv;
        }
        FENCE_ASYNC();
        __syncwarp();
        if (lane == 0) mbar_arrive(K1_BAR(17));
        if (warp == 8 && lane < 8) {
            mbar_wait(K1_BAR(17), 0);
            bulk_store(g_kvimg + (size_t)(hg * 8 + lane) * 196608 + mt * 12288, stg + lane * 12288, 12288);
            asm volatile("cp.async.bulk.commit_group;" ::: "memory");
        }
        __syncwarp();
        if (sel == 0) {
            float* kd = g_kn2 + (hg * 8) * 128 + mt * 8 + mh * 4 + w4;
            if (odd) k1_norms<true>(pk, lane, kd); else k1_norms<false>(pk, lane, kd);
        }
        do_gate = sel == 1;
    } else {
        k1_stage_rows(pk, stg + rg * 5120 + sel * 2560 + (lane >> 4) * 128 + (lane & 7) * 16, odd);
        FENCE_ASYNC();
        __syncwarp();
        if (lane == 0) mbar_arrive(K1_BAR(17));
        if (wg != 0) {
            const int mi = wg - 1;
            mbar_wait(K1_BAR(17), 0);
            float* kvo = (float*)(smem + 65536 + 81920);
            float kv[44], zz[4];
            #pragma unroll
            for (int i = 0; i < 44; i++) kv[i] = 0.f;
            zz[0] = zz[1] = zz[2] = zz[3] = 0.f;
            fence_f(kv); fence_f(zz);
            const int vs = mi == 0 ? 0 : (mi == 1 ? 56 : 72);
            const uint64_t da = mkdesc(stg + mi * 1024, 5120, 128, 0);
            const uint64_t db = mkdesc(stg + 2560 + (vs >> 3) * 128, 5120, 128, 0);
            const uint64_t d1 = mkdesc(sb + K1_ONES, 0, 128, 0);
            WG_FENCE();
            #pragma unroll
            for (int k = 0; k < 8; k++) {
                wg_ss_n88_atbt(kv, da + k * 640, db + k * 640, 1);
                wg_ss_n8_atbt(zz, da + k * 640, d1, 1);
            }
            WG_COMMIT();
            WG_WAIT(0);
            fence_f(kv); fence_f(zz);
            #pragma unroll
            for (int r = 0; r < 2; r++) {
                const int pc = mi * 64 + w4 * 16 + g + 8 * r;
                if (pc < 160) {
                    const int e0 = vs + 2 * t - (pc / 20) * 20;
                    #pragma unroll
                    for (int j = 0; j < 11; j++) {
                        const int e = e0 + 8 * j;
                        if (e >= 0 && e < 20) *(float2*)(kvo + pc * 24 + e) = make_float2(kv[4*j + 2*r], kv[4*j + 2*r + 1]);
                    }
                    if (t == 0) kvo[3840 + pc] = zz[2 * r];
                }
            }
            FENCE_ASYNC();
            __syncwarp();
            if (lane == 0) mbar_arrive(K1_BAR(18));
            if (tid == 256) {
                mbar_wait(K1_BAR(18), 0);
                bulk_store(g_kvpart + (size_t)(mt * NH + hg * 8) * 480, stg + 81920, 15360);
                bulk_store(g_zpart + (mt * NH + hg * 8) * 20, stg + 97280, 640);
                asm volatile("cp.async.bulk.commit_group;" ::: "memory");
            }
            __syncwarp();
        }
        do_gate = wg == 0;
    }
    if (do_gate) {
        const int nr = br ? 2 : 4;
        #pragma unroll 1
        for (int r0 = 0; r0 < nr; r0 += 2) {
            const int row = mt * 128 + grp * 16 + (warp & 7) * nr + r0;
            float s0 = 0.f, s1 = 0.f;
            uint4 v0[3], v1[3], w[3];
            #pragma unroll
            for (int c = 0; c < 3; c++) {
                const int ch = min(lane + 32 * c, 79);
                v0[c] = *(const uint4*)(x + row * DM + ch * 8); v1[c] = *(const uint4*)(x + (row + 1) * DM + ch * 8); w[c] = *(const uint4*)(gate_w + ch * 8);
            }
            if (lane >= 16) w[2] = make_uint4(0, 0, 0, 0);
            #pragma unroll
            for (int c = 0; c < 3; c++) {
                s0 += dot_bf(v0[c].x, w[c].x) + dot_bf(v0[c].y, w[c].y) + dot_bf(v0[c].z, w[c].z) + dot_bf(v0[c].w, w[c].w);
                s1 += dot_bf(v1[c].x, w[c].x) + dot_bf(v1[c].y, w[c].y) + dot_bf(v1[c].z, w[c].z) + dot_bf(v1[c].w, w[c].w);
            }
            #pragma unroll
            for (int o = 16; o; o >>= 1) { s0 += __shfl_xor_sync(0xffffffffu, s0, o); s1 += __shfl_xor_sync(0xffffffffu, s1, o); }
            if (lane < 2) g_gate[row + lane] = bfr(1.f / (1.f + __expf(-bfr(lane ? s1 : s0))));
        }
    }
    if (warp == 8) asm volatile("cp.async.bulk.wait_group.read 0;" ::: "memory");
}

#define K2_SMEM (196608 + 12288 + 1024)

struct PolyC { uint32_t one, c2; };
__device__ __forceinline__ uint32_t hfma2bf(uint32_t a, uint32_t b, uint32_t c) { uint32_t r; asm("fma.rn.bf16x2 %0, %1, %2, %3;" : "=r"(r) : "r"(a), "r"(b), "r"(c)); return r; }
__device__ __forceinline__ uint32_t exp2_poly2(float y0, float y1, const PolyC& pc) {
    const uint32_t sch = __byte_perm(__float_as_uint(y0), __float_as_uint(y1), 0x6521);
    uint32_t m; asm("lop3.b32 %0, %1, 0x007F007F, %2, 0xEA;" : "=r"(m) : "r"(sch), "r"(pc.one));
    return hfma2bf(hfma2bf(m, pc.c2, 0xC2FDC300u), m, 0x43AA43ABu) + sch;
}
template<int PAR>
__device__ __forceinline__ void softmax_blk(const float (&s)[32], uint32_t (&p)[16], const PolyC& pc) {
    #pragma unroll
    for (int j = 0; j < 8; j++) {
        if ((POLY_MASK >> (PAR * 8 + j)) & 1) {
            p[2*j] = exp2_poly2(s[4*j], s[4*j+1], pc);
            p[2*j+1] = exp2_poly2(s[4*j+2], s[4*j+3], pc);
        } else {
            p[2*j] = packbf(ex2f(s[4*j]), ex2f(s[4*j+1]));
            p[2*j+1] = packbf(ex2f(s[4*j+2]), ex2f(s[4*j+3]));
        }
    }
}

__device__ __noinline__ void aux_work(uint8_t* smem, int ax, const __nv_bfloat16* __restrict__ a_wo) {
    float* kvs = (float*)smem;
    const int tid = threadIdx.x;
    for (int i = tid; i < 3840; i += 512) {
        float s = 0.f;
        #pragma unroll
        for (int m = 0; m < 16; m++) s += g_kvpart[(size_t)(m * NH + ax * 8) * 480 + i];
        kvs[i] = s;
    }
    __syncthreads();
    #pragma unroll 1
    for (int it = tid; it < 8 * 5 * 80; it += 512) {
        const int cc = it % 80, dq = (it / 80) % 5, h = it / 400;
        float a[4][8];
        #pragma unroll
        for (int r = 0; r < 4; r++)
            #pragma unroll
            for (int i = 0; i < 8; i++) a[r][i] = 0.f;
        const __nv_bfloat16* wp = a_wo + (size_t)((ax * 8 + h) * DH) * DM + cc * 8;
        const float* kp = kvs + (h * 20 + dq * 4) * 24;
        #pragma unroll 5
        for (int e = 0; e < 20; e++) {
            const uint4 w = *(const uint4*)(wp + e * DM);
            const float wf[8] = {bflo(w.x), bfhi(w.x), bflo(w.y), bfhi(w.y), bflo(w.z), bfhi(w.z), bflo(w.w), bfhi(w.w)};
            #pragma unroll
            for (int r = 0; r < 4; r++) {
                const float k = kp[r * 24 + e];
                #pragma unroll
                for (int i = 0; i < 8; i++) a[r][i] += k * wf[i];
            }
        }
        #pragma unroll
        for (int r = 0; r < 4; r++)
            *(uint4*)(g_wm + (size_t)((ax * 8 + h) * DH + dq * 4 + r) * DM + cc * 8) =
                make_uint4(packbf(a[r][0], a[r][1]), packbf(a[r][2], a[r][3]), packbf(a[r][4], a[r][5]), packbf(a[r][6], a[r][7]));
    }
}

__global__ void __launch_bounds__(512, 1)
attn_kernel(const __nv_bfloat16* __restrict__ a_wo) {
    extern __shared__ __align__(1024) uint8_t smem[];
    const uint32_t sb = smem_u32(smem);
    const uint32_t bars = sb + 196608 + 12288;
    const int tid = threadIdx.x, warp = tid >> 5, lane = tid & 31;
    GRIDDEP_LAUNCH();
    if (blockIdx.x < 4) {
        GRIDDEP_WAIT();
        aux_work(smem, blockIdx.x, a_wo);
        return;
    }
    const int h = (blockIdx.x - 4) >> 2, qb = blockIdx.x & 3;
    if (tid == 0) {
        for (int i = 0; i < 17; i++) mbar_init(bars + 8 * i, 1);
        asm volatile("fence.mbarrier_init.release.cluster;" ::: "memory");
        mbar_arrive(bars + 128);
    }
    GRIDDEP_WAIT();
    const int wg = warp >> 2, w4 = warp & 3, g = lane >> 2, t = lane & 3;
    const uint8_t* kvsrc = g_kvimg + (size_t)h * 196608;
    if (tid == 0) {
        for (int i = 0; i < 2; i++) { mbar_expect(bars + 8 * i, 12288); bulk_load(sb + i * 12288, kvsrc + i * 12288, 12288, bars + 8 * i); }
    }
    const int rbase = qb * 512 + wg * 128 + w4 * 16 + g;
    const int fb = (5 * h) >> 1;
    const bool odd = h & 1;
    const bool cslot = odd ? t < 2 : t >= 2;
    const uint32_t qo = ((rbase >> 3) * 80 + fb) * 128 + lane * 4;
    uint32_t qv[2][3];
    float kmax, gt[4] = {0.f, 0.f, 0.f, 0.f};
    {
        #pragma unroll
        for (int r = 0; r < 2; r++) {
            qv[r][0] = *(const uint32_t*)(g_qb + qo + r * 10240); qv[r][1] = *(const uint32_t*)(g_qb + qo + r * 10240 + 128); qv[r][2] = *(const uint32_t*)(g_qb + qo + r * 10240 + 256);
        }
        const float4 kn4 = *(const float4*)(g_kn2 + h * 128 + lane * 4);
        float kn = fmaxf(fmaxf(kn4.x, kn4.y), fmaxf(kn4.z, kn4.w));
        #pragma unroll
        for (int o = 16; o; o >>= 1) kn = fmaxf(kn, __shfl_xor_sync(0xffffffffu, kn, o));
        kmax = sqrtf(kn);
        __syncthreads();
        if (tid == 256) {
            for (int i = 2; i < 16; i++) { mbar_expect(bars + 8 * i, 12288); bulk_load(sb + i * 12288, kvsrc + i * 12288, 12288, bars + 8 * i); }
        }
        __syncwarp();
    }
    PolyC pc;
    pc.c2 = 0x42274229u + blockIdx.y;
    pc.one = 0x3F803F80u + blockIdx.y;

    #pragma unroll 1
    for (int tile = 0; tile < 2; tile++) {
        const int row0 = rbase + tile * 64;
        uint32_t q[8];
        if (cslot) { if (odd) { qv[0][0] = 0u; qv[1][0] = 0u; } else { qv[0][2] = 0u; qv[1][2] = 0u; } }
        q[0] = qv[0][0]; q[1] = qv[1][0]; q[2] = qv[0][1]; q[3] = qv[1][1]; q[4] = qv[0][2]; q[5] = qv[1][2];
        q[6] = blockIdx.y; q[7] = blockIdx.y;
        float n0 = bflo(q[0]) * bflo(q[0]) + bfhi(q[0]) * bfhi(q[0]) + bflo(q[2]) * bflo(q[2]) + bfhi(q[2]) * bfhi(q[2]) + bflo(q[4]) * bflo(q[4]) + bfhi(q[4]) * bfhi(q[4]);
        float n1 = bflo(q[1]) * bflo(q[1]) + bfhi(q[1]) * bfhi(q[1]) + bflo(q[3]) * bflo(q[3]) + bfhi(q[3]) * bfhi(q[3]) + bflo(q[5]) * bflo(q[5]) + bfhi(q[5]) * bfhi(q[5]);
        n0 += __shfl_xor_sync(0xffffffffu, n0, 1); n1 += __shfl_xor_sync(0xffffffffu, n1, 1);
        n0 += __shfl_xor_sync(0xffffffffu, n0, 2); n1 += __shfl_xor_sync(0xffffffffu, n1, 2);
        const float m0 = sqrtf(n0) * kmax * 1.02f + 0.0625f, m1 = sqrtf(n1) * kmax * 1.02f + 0.0625f;
        uint32_t unsafe = !(m0 <= 48.f && m1 <= 48.f);
        asm volatile("{.reg .pred p, q; setp.ne.u32 p, %0, 0; barrier.red.or.pred q, %1, 128, p; selp.u32 %0, 1, 0, q;}" : "+r"(unsafe) : "r"(wg + 1) : "memory");
        unsafe = __any_sync(0xffffffffu, unsafe);

        float o[12];
        #pragma unroll
        for (int i = 0; i < 12; i++) o[i] = 0.f;
        fence_f(o);
        const uint64_t dk = mkdesc(sb, 128, 768, 0), dk2 = mkdesc(sb + 256, 0, 768, 0), dv = mkdesc(sb + 384, 768, 128, 0);
        float S[32];
        uint32_t p[16];
        if (!unsafe) {
            if (cslot) {
                const uint32_t c0 = (t & 1) ? 0x3B80u : ((packbf(-m0, 0.f) & 0xFFFFu) | 0x43FC0000u);
                const uint32_t c1 = (t & 1) ? 0x3B80u : ((packbf(-m1, 0.f) & 0xFFFFu) | 0x43FC0000u);
                if (odd) { q[0] = c0; q[1] = c1; } else { q[4] = c0; q[5] = c1; }
            }
            uint64_t ck = dk, ck2 = dk2, cv = dv;
            uint32_t cb = bars;
            mbar_wait(cb, 0);
            WG_FENCE();
            wg_qk0(S, q[0], q[1], q[2], q[3], ck); wg_qk1(S, q[4], q[5], q[6], q[7], ck2);
            WG_COMMIT();
            WG_WAIT(0);
            fence_f(S);
            #pragma unroll 1
            for (int c = 0; c < 16; c++) {
                softmax_blk<0>(S, p, pc);
                fence_r(p);
                WG_FENCE();
                wg_qk0(S, q[0], q[1], q[2], q[3], ck + 384); wg_qk1(S, q[4], q[5], q[6], q[7], ck2 + 384);
                #pragma unroll
                for (int k = 0; k < 4; k++) wg_pv(o, p[4*k], p[4*k+1], p[4*k+2], p[4*k+3], cv + k * 96);
                WG_COMMIT();
                WG_WAIT(0);
                fence_f(S);
                softmax_blk<1>(S, p, pc);
                fence_r(p);
                cb += 8; ck += 768; ck2 += 768;
                mbar_wait(cb, 0);
                WG_FENCE();
                wg_qk0(S, q[0], q[1], q[2], q[3], ck); wg_qk1(S, q[4], q[5], q[6], q[7], ck2);
                #pragma unroll
                for (int k = 0; k < 4; k++) wg_pv(o, p[4*k], p[4*k+1], p[4*k+2], p[4*k+3], cv + 384 + k * 96);
                WG_COMMIT();
                cv += 768;
                WG_WAIT(0);
                fence_f(S);
            }
        } else {
            float rm0 = -INFINITY, rm1 = -INFINITY;
            #pragma unroll 1
            for (int b = 0; b < 32; b++) {
                if ((b & 1) == 0) mbar_wait(bars + 8 * (b >> 1), 0);
                WG_FENCE();
                wg_qk0(S, q[0], q[1], q[2], q[3], dk + b * 384); wg_qk1(S, q[4], q[5], q[6], q[7], dk2 + b * 384);
                WG_COMMIT();
                WG_WAIT(0);
                fence_f(S);
                float x0 = rm0, x1 = rm1;
                #pragma unroll
                for (int j = 0; j < 8; j++) { x0 = fmaxf(x0, fmaxf(S[4*j], S[4*j+1])); x1 = fmaxf(x1, fmaxf(S[4*j+2], S[4*j+3])); }
                x0 = fmaxf(x0, __shfl_xor_sync(0xffffffffu, x0, 1)); x1 = fmaxf(x1, __shfl_xor_sync(0xffffffffu, x1, 1));
                x0 = fmaxf(x0, __shfl_xor_sync(0xffffffffu, x0, 2)); x1 = fmaxf(x1, __shfl_xor_sync(0xffffffffu, x1, 2));
                const float c0 = ex2f(rm0 - x0), c1 = ex2f(rm1 - x1);
                rm0 = x0; rm1 = x1;
                #pragma unroll
                for (int j = 0; j < 3; j++) { o[4*j] *= c0; o[4*j+1] *= c0; o[4*j+2] *= c1; o[4*j+3] *= c1; }
                #pragma unroll
                for (int j = 0; j < 8; j++) {
                    p[2*j] = packbf(ex2f(S[4*j] - x0), ex2f(S[4*j+1] - x0));
                    p[2*j+1] = packbf(ex2f(S[4*j+2] - x1), ex2f(S[4*j+3] - x1));
                }
                fence_r(p); fence_f(o);
                WG_FENCE();
                #pragma unroll
                for (int k = 0; k < 4; k++) wg_pv(o, p[4*k], p[4*k+1], p[4*k+2], p[4*k+3], dv + b * 384 + k * 96);
                WG_COMMIT();
                WG_WAIT(0);
                fence_f(o);
            }
        }
        fence_f(o);
        const int src = (lane & ~3) | (odd ? 0 : 2);
        const float l0 = __shfl_sync(0xffffffffu, odd ? o[0] : o[8], src), l1 = __shfl_sync(0xffffffffu, odd ? o[2] : o[10], src);
        if (tile == 0) {
            uint32_t pv[4][3];
            float zs = 0.f;
            #pragma unroll
            for (int r = 0; r < 4; r++) {
                const uint32_t po = qo + ((r & 1) + (r >> 1) * 8) * 10240;
                pv[r][0] = *(const uint32_t*)(g_pq + po); pv[r][1] = *(const uint32_t*)(g_pq + po + 128); pv[r][2] = *(const uint32_t*)(g_pq + po + 256);
                gt[r] = g_gate[rbase + (r & 1) * 8 + (r >> 1) * 64];
            }
            #pragma unroll
            for (int r = 0; r < 2; r++) {
                qv[r][0] = *(const uint32_t*)(g_qb + qo + 81920 + r * 10240); qv[r][1] = *(const uint32_t*)(g_qb + qo + 81920 + r * 10240 + 128);
                qv[r][2] = *(const uint32_t*)(g_qb + qo + 81920 + r * 10240 + 256);
            }
            const int d = lane - (odd ? 4 : 0);
            if (d >= 0 && d < 20) {
                #pragma unroll
                for (int m = 0; m < 16; m++) zs += g_zpart[(m * NH + h) * 20 + d];
            }
            float z[6];
            #pragma unroll
            for (int j = 0; j < 3; j++) { z[2*j] = __shfl_sync(0xffffffffu, zs, 8 * j + 2 * t); z[2*j+1] = __shfl_sync(0xffffffffu, zs, 8 * j + 2 * t + 1); }
            #pragma unroll
            for (int r = 0; r < 4; r++) {
                float den = bflo(pv[r][0]) * z[0] + bfhi(pv[r][0]) * z[1] + bflo(pv[r][1]) * z[2] + bfhi(pv[r][1]) * z[3] + bflo(pv[r][2]) * z[4] + bfhi(pv[r][2]) * z[5];
                den += __shfl_xor_sync(0xffffffffu, den, 1);
                den += __shfl_xor_sync(0xffffffffu, den, 2);
                const float sc = gt[r] / (den + 1e-6f);
                const int tg = (rbase >> 3) + (r & 1) + (r >> 1) * 8;
                #pragma unroll
                for (int j = 0; j < 3; j++) {
                    const int kb = fb + j;
                    if (!(cslot && j == (odd ? 0 : 2)))
                        *(uint32_t*)(g_acat + (((kb >> 3) * 256 + tg) * 8 + (kb & 7)) * 128 + lane * 4) = packbf(bflo(pv[r][j]) * sc, bfhi(pv[r][j]) * sc);
                }
            }
        } else { gt[0] = gt[2]; gt[1] = gt[3]; }
        const float s0 = bfr(1.f - gt[0]) / l0, s1 = bfr(1.f - gt[1]) / l1;
        #pragma unroll
        for (int j = 0; j < 3; j++) {
            const int kb = 80 + fb + j;
            uint8_t* dst = g_acat + (((kb >> 3) * 256 + (row0 >> 3)) * 8 + (kb & 7)) * 128 + lane * 4;
            if (!(cslot && j == (odd ? 0 : 2))) {
                *(uint32_t*)dst = packbf(o[4*j] * s0, o[4*j+1] * s0);
                *(uint32_t*)(dst + 1024) = packbf(o[4*j+2] * s1, o[4*j+3] * s1);
            }
        }
    }
}

__constant__ uint8_t k3_map[130] = {0,1,2,3,16,17,18,19,32,33,34,35,48,49,50,51,4,5,6,7,20,21,22,23,36,37,38,39,52,53,54,55,8,9,24,25,40,41,56,57,64,65,66,67,80,81,82,83,96,97,98,99,112,113,114,115,68,69,70,71,84,85,86,87,100,101,102,103,116,117,118,119,72,73,88,89,104,105,120,121,128,129,130,131,144,145,146,147,160,161,162,163,176,177,178,179,132,133,134,135,148,149,150,151,164,165,166,167,180,181,182,183,136,137,152,153,168,169,184,185,192,193,194,195,196,197,198,199,200,201};
#define K3_STAGE 28672
#define K3_NST 6
#define K3_SMEM (K3_NST * K3_STAGE + 1024)
__global__ void __launch_bounds__(160, 1)
out_kernel(const __grid_constant__ CUtensorMap tm_wm, const __grid_constant__ CUtensorMap tm_wob,
           __nv_bfloat16* __restrict__ out) {
    extern __shared__ __align__(1024) uint8_t smem[];
    const uint32_t sb = smem_u32(smem);
    const uint32_t bar_full = sb + K3_NST * K3_STAGE, bar_empty = bar_full + 64;
    const int tid = threadIdx.x, warp = tid >> 5, lane = tid & 31;
    const int tt = k3_map[blockIdx.x] >> 4, ct = k3_map[blockIdx.x] & 15;
    if (tid == 0) {
        for (int i = 0; i < K3_NST; i++) { mbar_init(bar_full + 8 * i, 1); mbar_init(bar_empty + 8 * i, 4); }
        asm volatile("fence.mbarrier_init.release.cluster;" ::: "memory");
    }
    __syncthreads();
    if (warp == 4) {
        if (lane == 0) {
            const uint32_t abytes = tt == 12 ? 16384 : 20480;
            for (int it = 0; it < K3_NST; it++) {
                mbar_expect(bar_full + 8 * it, 8192 + abytes);
                tma2d(sb + it * K3_STAGE, &tm_wob, bar_full + 8 * it, ct * 64, it * 64);
            }
            GRIDDEP_WAIT();
            for (int it = 0; it < 20; it++) {
                const int s = it % K3_NST;
                const uint32_t st = sb + s * K3_STAGE, fb = bar_full + 8 * s;
                if (it >= K3_NST) {
                    mbar_wait(bar_empty + 8 * s, ((it / K3_NST) - 1) & 1);
                    mbar_expect(fb, 8192 + abytes);
                    tma2d(st, it < 10 ? &tm_wob : &tm_wm, fb, ct * 64, (it % 10) * 64);
                }
                bulk_load(st + 8192, g_acat + (size_t)(((it + 10) % 20) * 256 + tt * 20) * 1024, abytes, fb);
            }
        }
    } else {
        float acc[80];
        #pragma unroll
        for (int i = 0; i < 80; i++) acc[i] = 0.f;
        fence_f(acc);
        for (int it = 0; it < 20; it++) {
            const int s = it % K3_NST;
            mbar_wait(bar_full + 8 * s, (it / K3_NST) & 1);
            const uint32_t st = sb + s * K3_STAGE;
            const uint64_t da = mkdesc(st, 8192, 1024, 1), db = mkdesc(st + 8192, 128, 1024, 0);
            WG_FENCE();
            #pragma unroll
            for (int k = 0; k < 4; k++) wg_ss_n160_at(acc, da + k * 128, db + k * 16, 1);
            WG_COMMIT();
            WG_WAIT(1);
            if (it > 0 && lane == 0) mbar_arrive(bar_empty + 8 * ((it - 1) % K3_NST));
        }
        WG_WAIT(0);
        fence_f(acc);
        named_bar(1, 128);
        #pragma unroll
        for (int j = 0; j < 20; j += 2) {
            const int tok = 8 * (j + (lane >> 4)) + (lane & 7);
            const int chunk = (2 * warp + ((lane >> 3) & 1)) ^ (tok & 7);
            const uint32_t addr = sb + tok * 128 + chunk * 16;
            asm volatile("stmatrix.sync.aligned.m8n8.x4.trans.shared.b16 [%0], {%1,%2,%3,%4};" :: "r"(addr),
                "r"(packbf(acc[4*j], acc[4*j+1])), "r"(packbf(acc[4*j+2], acc[4*j+3])), "r"(packbf(acc[4*j+4], acc[4*j+5])), "r"(packbf(acc[4*j+6], acc[4*j+7])) : "memory");
        }
        named_bar(1, 128);
        #pragma unroll
        for (int i = 0; i < 10; i++) {
            const int idx = tid + 128 * i, tok = idx >> 3, ch = idx & 7;
            const int gtok = tt * 160 + tok;
            const uint4 v = *(const uint4*)(smem + tok * 128 + ((ch ^ (tok & 7)) * 16));
            if (gtok < SEQ) *(uint4*)(out + (size_t)gtok * DM + ct * 64 + ch * 8) = v;
        }
    }
}

typedef CUresult (*PFN_tmapEncode)(CUtensorMap*, CUtensorMapDataType, cuuint32_t, void*, const cuuint64_t*, const cuuint64_t*, const cuuint32_t*, const cuuint32_t*,
                                   CUtensorMapInterleave, CUtensorMapSwizzle, CUtensorMapL2promotion, CUtensorMapFloatOOBfill);
static void make_map(PFN_tmapEncode enc, CUtensorMap* tm, const void* ptr, uint64_t cols, uint64_t rows, uint32_t bcols, uint32_t brows) {
    cuuint64_t gd[2] = {cols, rows}; cuuint64_t gs[1] = {cols * 2}; cuuint32_t bx[2] = {bcols, brows}; cuuint32_t es[2] = {1, 1};
    enc(tm, CU_TENSOR_MAP_DATA_TYPE_BFLOAT16, 2, (void*)ptr, gd, gs, bx, es, CU_TENSOR_MAP_INTERLEAVE_NONE, CU_TENSOR_MAP_SWIZZLE_128B,
        CU_TENSOR_MAP_L2_PROMOTION_L2_128B, CU_TENSOR_MAP_FLOAT_OOB_FILL_NONE);
}

extern "C" void kernel_launch(void* const* d_in, const int* in_sizes, int n_in, void* d_out, int out_size) {
    const __nv_bfloat16* x = (const __nv_bfloat16*)d_in[0];
    const __nv_bfloat16* a_wqkv = (const __nv_bfloat16*)d_in[1];
    const __nv_bfloat16* a_wo = (const __nv_bfloat16*)d_in[2];
    const __nv_bfloat16* b_wqkv = (const __nv_bfloat16*)d_in[4];
    const __nv_bfloat16* b_wo = (const __nv_bfloat16*)d_in[5];
    const __nv_bfloat16* gate_w = (const __nv_bfloat16*)d_in[6];
    static CUtensorMap tm_x, tm_wm, tm_wob;
    static WMaps tm_w;
    static const void* cached[4] = {nullptr, nullptr, nullptr, nullptr};
    if (cached[0] != x || cached[1] != a_wqkv || cached[2] != b_wqkv || cached[3] != b_wo) {
        void* fn = nullptr; cudaDriverEntryPointQueryResult qr;
        cudaGetDriverEntryPoint("cuTensorMapEncodeTiled", &fn, cudaEnableDefault, &qr);
        PFN_tmapEncode enc = (PFN_tmapEncode)fn;
        void* p_wm;
        cudaGetSymbolAddress(&p_wm, g_wm);
        make_map(enc, &tm_x, x, DM, SEQ, 64, 128);
        for (int i = 0; i < 4; i++) {
            cuuint64_t gd[4] = {64, DM, 10, 3}; cuuint64_t gs[3] = {3 * DM * 2, 128, DM * 2};
            cuuint32_t bx[4] = {64, 64, 3, (cuuint32_t)((i & 1) ? 1 : 2)}; cuuint32_t es[4] = {1, 1, 1, 1};
            enc(&tm_w.m[i], CU_TENSOR_MAP_DATA_TYPE_BFLOAT16, 4, (void*)(i < 2 ? a_wqkv : b_wqkv), gd, gs, bx, es, CU_TENSOR_MAP_INTERLEAVE_NONE,
                CU_TENSOR_MAP_SWIZZLE_128B, CU_TENSOR_MAP_L2_PROMOTION_L2_128B, CU_TENSOR_MAP_FLOAT_OOB_FILL_NONE);
        }
        make_map(enc, &tm_wm, p_wm, DM, DM, 64, 64);
        make_map(enc, &tm_wob, b_wo, DM, DM, 64, 64);
        cudaFuncSetAttribute(qkv_kernel, cudaFuncAttributeMaxDynamicSharedMemorySize, K1_SMEM);
        cudaFuncSetAttribute(attn_kernel, cudaFuncAttributeMaxDynamicSharedMemorySize, K2_SMEM);
        cudaFuncSetAttribute(out_kernel, cudaFuncAttributeMaxDynamicSharedMemorySize, K3_SMEM);
        cached[0] = x; cached[1] = a_wqkv; cached[2] = b_wqkv; cached[3] = b_wo;
    }
    cudaStream_t st = cudaStreamPerThread;
    cudaLaunchAttribute at[1];
    at[0].id = cudaLaunchAttributeProgrammaticStreamSerialization; at[0].val.programmaticStreamSerializationAllowed = 1;
    cudaLaunchConfig_t cfg = {};
    cfg.stream = st;
    cfg.gridDim = dim3(128); cfg.blockDim = dim3(512); cfg.dynamicSmemBytes = K1_SMEM; cfg.attrs = at; cfg.numAttrs = 0;
    cudaLaunchKernelEx(&cfg, qkv_kernel, tm_x, tm_w, x, gate_w);
    cfg.gridDim = dim3(132); cfg.blockDim = dim3(512); cfg.dynamicSmemBytes = K2_SMEM; cfg.numAttrs = 1;
    cudaLaunchKernelEx(&cfg, attn_kernel, a_wo);
    cfg.gridDim = dim3(130); cfg.blockDim = dim3(160); cfg.dynamicSmemBytes = K3_SMEM; cfg.numAttrs = 1;
    cudaLaunchKernelEx(&cfg, out_kernel, tm_wm, tm_wob, (__nv_bfloat16*)d_out);
}
```
